```python
import torch

def _softmax(x, axis=-1):
    return torch.softmax(x, dim=axis)
def _gelu(x):
    return torch.nn.functional.gelu(x, approximate="tanh")
def _silu(x):
    return torch.nn.functional.silu(x)
def _sigmoid(x):
    return torch.sigmoid(x)
def _layernorm(x, axis=-1, eps=1e-5):
    m = x.mean(dim=axis, keepdim=True)
    v = x.var(dim=axis, keepdim=True, unbiased=False)
    return (x - m) / torch.sqrt(v + eps)
def _scatter_add(tgt, idx, src, axis=0):
    return tgt.clone().index_add_(axis, idx, src)
def _segment_sum(src, seg, n):
    out = torch.zeros((n,) + src.shape[1:], dtype=src.dtype)
    return out.index_add_(0, seg, src)
def _pad(x, pw):
    flat = tuple(v for pair in reversed(pw) for v in pair)
    return torch.nn.functional.pad(x, flat)

kernel_name = 'concat_heads__compressed_kv_cla__mha_block_cached__decode'

def setup_inputs():

    _w = (lambda a: (lambda t: t.to(torch.bfloat16) if t.is_floating_point() else t)(torch.as_tensor(a)))
    def _A_setup():
        B, H, Sq, Sk, D, M = 4, 32, 1, 4096, 128, 512
        Dc = 4 * D
        return {
            "x": _w((lambda *s: torch.randn(*s, dtype=torch.bfloat16) * 3.2)(B, Sq, M)),
            "c_kv": _w((lambda *s: torch.randn(*s, dtype=torch.bfloat16) * 0.1)(B, Sk, Dc)),
            "w_q": _w((lambda *s: torch.randn(*s, dtype=torch.bfloat16) * 6.4)(M, H, D) * (M ** -0.5)),
            "w_uk": _w((lambda *s: torch.randn(*s, dtype=torch.bfloat16) * 6.4)(Dc, H, D) * (Dc ** -0.5)),
            "w_uv": _w((lambda *s: torch.randn(*s, dtype=torch.bfloat16) * 0.1)(Dc, H, D) * (Dc ** -0.5)),
            "w_o": _w((lambda *s: torch.randn(*s, dtype=torch.bfloat16) * 0.1)(H, D, M) * ((H * D) ** -0.5)),
        }
    _A_in = _A_setup()

    def _B_setup():
        B, Sq, D = 4, 1, 512
        H, Sk, Dh = 32, 4096, 128
        return {
            "x": _w((lambda *s: torch.randn(*s, dtype=torch.bfloat16) * 1.6)(B, Sq, D)),
            "k_cache": _w((lambda *s: torch.randn(*s, dtype=torch.bfloat16) * 1.6)(B, H, Sk, Dh)),
            "v_cache": _w((lambda *s: torch.randn(*s, dtype=torch.bfloat16) * 0.05)(B, H, Sk, Dh)),
            "wq": _w((lambda *s: torch.randn(*s, dtype=torch.bfloat16) * 1.6)(D, H * Dh) * (D ** -0.5)),
            "wo": _w((lambda *s: torch.randn(*s, dtype=torch.bfloat16) * 0.05)(H * Dh, D) * ((H * Dh) ** -0.5)),
        }
    _B_in = _B_setup()

    return {
        "A_x": _A_in["x"],
        "A_c_kv": _A_in["c_kv"],
        "A_w_q": _A_in["w_q"],
        "A_w_uk": _A_in["w_uk"],
        "A_w_uv": _A_in["w_uv"],
        "A_w_o": _A_in["w_o"],
        "B_x": _B_in["x"],
        "B_k_cache": _B_in["k_cache"],
        "B_v_cache": _B_in["v_cache"],
        "B_wq": _B_in["wq"],
        "B_wo": _B_in["wo"],
    }

def reference(A_x, A_c_kv, A_w_q, A_w_uk, A_w_uv, A_w_o, B_x, B_k_cache, B_v_cache, B_wq, B_wo):
    def _A_ref(x, c_kv, w_q, w_uk, w_uv, w_o):
        B, Sq, M = x.shape[0], x.shape[1], x.shape[2]
        Sk = c_kv.shape[1]
        H, D = w_q.shape[1], w_q.shape[2]
        q = torch.einsum("bqm,mhd->bhqd", x, w_q)
        k = torch.einsum("bkc,chd->bhkd", c_kv, w_uk)
        v = torch.einsum("bkc,chd->bhkd", c_kv, w_uv)
        scores = torch.einsum("bhqd,bhkd->bhqk", q, k) * (D ** -0.5)
        off = Sk - Sq
        qi = torch.arange(Sq)[:, None]
        kj = torch.arange(Sk)[None, :]
        cmask = kj <= (qi + off)
        scores = torch.where(cmask[None, None], scores, -1e9)
        p = _softmax(scores, axis=-1)
        ctx = torch.einsum("bhqk,bhkd->bhqd", p, v)
        return torch.einsum("bhqd,hdm->bqm", ctx, w_o)

    def _B_ref(x, k_cache, v_cache, wq, wo):
        B, Sq, D = x.shape
        H, Dh = 32, 128
        q = (lambda x, *d: x.permute(*d))((x @ wq).reshape(B, Sq, H, Dh), 0, 2, 1, 3)
        scores = torch.einsum("bhqd,bhkd->bhqk", q, k_cache) * (Dh ** -0.5)
        p = _softmax(scores, axis=-1)
        o = torch.einsum("bhqk,bhkd->bhqd", p, v_cache)
        return (lambda x, *d: x.permute(*d))(o, 0, 2, 1, 3).reshape(B, Sq, H * Dh) @ wo

    a = _A_ref(A_x, A_c_kv, A_w_q, A_w_uk, A_w_uv, A_w_o)
    b = _B_ref(B_x, B_k_cache, B_v_cache, B_wq, B_wo)
    return torch.concatenate([a, b], axis=-1)
```

```cpp
#include <cuda_runtime.h>
#include <cuda.h>
#include <cuda_bf16.h>
#include <stdint.h>

namespace {

constexpr int NCTA      = 128;
constexpr int NTHREADS  = 512;
constexpr int CH_BYTES  = 16384;
constexpr int NPIECE    = 128 * 64;
constexpr int RING      = 8;
#define WIN 3
#define DL0 3000
#define DLS 1000
#define NB2 4400
#define NBS 1300
#define DLR 18
#define HS 30
#define XS 224
#define TG 5700
#define LAG 192
#define LAG2 64
#define LAG1 192
#define HURG 24
#define FSLEEP 600
#define QSLEEP 400
#define QD0 600
#define QD1 100
#define TRIG0 (20 * 128)
#define TRIG1 (32 * 128)
#define TRIG2 (50 * 128)
constexpr int SMEM_EXTRA = 0;
constexpr int A_SPLITS  = 8;
constexpr int A_TILES   = 4096 / A_SPLITS / 16;

constexpr int OFF_RING  = 0;
constexpr int OFF_XR    = OFF_RING + RING * CH_BYTES;
constexpr int OFF_SS    = OFF_XR + 4 * CH_BYTES;
constexpr int OFF_SP    = OFF_SS + 8 * 32 * 80;
constexpr int OFF_ALPHA = OFF_SP + 1024;
constexpr int OFF_OA    = OFF_ALPHA + 128;
constexpr int OFF_ST    = OFF_OA + 4 * 288;
constexpr int OFF_MLA   = OFF_ST + 64 * 32;
constexpr int OFF_QT    = OFF_MLA + 4 * A_SPLITS * 8;
constexpr int MG_BYTES  = 2048 + 128 + 32;
constexpr int OFF_MG    = OFF_QT + 4 * 256;
constexpr int OFF_META  = OFF_MG + 2 * MG_BYTES;
constexpr int OFF_EP    = OFF_META + 16;
constexpr int OFF_X     = OFF_SS + 4096;
constexpr int OFF_BAR   = OFF_EP + 16;
constexpr int NBAR      = 2 * RING + 8 + 2 + 3 + 4 + 3 + 1 + 8 + 8 + 2 + 2 + 2 + 1;
constexpr int I_INI     = 2 * RING + 8 + 2 + 3 + 4 + 3;
constexpr int SMEM_BYTES = OFF_BAR + NBAR * 8;

constexpr float LOG2E = 1.4426950408889634f;
constexpr float SCALE = 0.08838834764831845f;
constexpr uint32_t SPIN_LIMIT = 1u << 20;

struct Scratch {
    uint32_t ticket[2][64];
    uint32_t epoch[NCTA];
    uint32_t cntQ[64], cntA[64];
    float2   mlA[32][4][A_SPLITS];
    uint32_t vec[2][32][4][128];
    uint32_t q[2][4][4096];
    uint16_t qabs[4][8][2][4][2][32][8];
    float    pA[32][4][A_SPLITS][512];
    uint32_t pB[NPIECE][128];
    uint32_t mlB[NPIECE][8];
};
__device__ __align__(128) Scratch g_scratch;
#define TL(i) do {} while (0)
#define TL3(i, dep) do {} while (0)
#define TLG(i) do {} while (0)
#define TL2(i) do {} while (0)

struct Hot {
    const char *kp, *vp;
    Scratch* S;
    const __nv_bfloat16* x[2];
    uint32_t zero;
};
struct Params {
    CUtensorMap tm_wq[2];
    CUtensorMap tm_wuk, tm_wuv;
    CUtensorMap tm_wo[2];
    CUtensorMap tm_ckv;
    const __nv_bfloat16* wo[2];
    __nv_bfloat16* out;
};

__device__ __forceinline__ void mbar_init(uint32_t bar, uint32_t cnt) {
    asm volatile("mbarrier.init.shared::cta.b64 [%0], %1;" :: "r"(bar), "r"(cnt) : "memory");
}
__device__ __forceinline__ void mbar_expect_tx(uint32_t bar, uint32_t bytes) {
    asm volatile("mbarrier.arrive.expect_tx.shared::cta.b64 _, [%0], %1;" :: "r"(bar), "r"(bytes) : "memory");
}
__device__ __forceinline__ void mbar_arrive(uint32_t bar) {
    asm volatile("mbarrier.arrive.shared::cta.b64 _, [%0];" :: "r"(bar) : "memory");
}
template <uint32_t LIMIT = SPIN_LIMIT>
__device__ __forceinline__ bool mbar_wait(uint32_t bar, uint32_t parity) {
    uint32_t done, it = 0;
    do {
        asm volatile("{\n.reg .pred p;\nmbarrier.try_wait.parity.shared::cta.b64 p, [%1], %2;\nselp.u32 %0, 1, 0, p;\n}"
                     : "=r"(done) : "r"(bar), "r"(parity) : "memory");
        if (++it > LIMIT) break;
    } while (!done);
    return done;
}
__device__ __forceinline__ void bulk_load(uint32_t dst, const void* src, uint32_t bytes, uint32_t bar, uint64_t pol) {
    asm volatile("cp.async.bulk.shared::cluster.global.mbarrier::complete_tx::bytes.L2::cache_hint [%0], [%1], %2, [%3], %4;"
                 :: "r"(dst), "l"(src), "r"(bytes), "r"(bar), "l"(pol) : "memory");
}
__device__ __forceinline__ uint64_t policy_evict_first() {
    uint64_t pol;
    asm volatile("createpolicy.fractional.L2::evict_first.b64 %0, 1.0;" : "=l"(pol));
    return pol;
}
__device__ __forceinline__ void bar_sync(int id, int n)   { asm volatile("bar.sync %0, %1;" :: "r"(id), "r"(n) : "memory"); }
__device__ __forceinline__ void bar_arrive(int id, int n) { asm volatile("bar.arrive %0, %1;" :: "r"(id), "r"(n) : "memory"); }
__device__ __forceinline__ void ldsm4(uint32_t (&r)[4], uint32_t addr) {
    asm volatile("ldmatrix.sync.aligned.m8n8.x4.shared.b16 {%0,%1,%2,%3}, [%4];"
                 : "=r"(r[0]), "=r"(r[1]), "=r"(r[2]), "=r"(r[3]) : "r"(addr) : "memory");
}
__device__ __forceinline__ void ldsm4t(uint32_t (&r)[4], uint32_t addr) {
    asm volatile("ldmatrix.sync.aligned.m8n8.x4.trans.shared.b16 {%0,%1,%2,%3}, [%4];"
                 : "=r"(r[0]), "=r"(r[1]), "=r"(r[2]), "=r"(r[3]) : "r"(addr) : "memory");
}
__device__ __forceinline__ void mma(float (&c)[4], uint32_t a0, uint32_t a1, uint32_t a2, uint32_t a3, uint32_t b0, uint32_t b1) {
    asm volatile("mma.sync.aligned.m16n8k16.row.col.f32.bf16.bf16.f32 {%0,%1,%2,%3}, {%4,%5,%6,%7}, {%8,%9}, {%0,%1,%2,%3};"
                 : "+f"(c[0]), "+f"(c[1]), "+f"(c[2]), "+f"(c[3])
                 : "r"(a0), "r"(a1), "r"(a2), "r"(a3), "r"(b0), "r"(b1));
}
__device__ __forceinline__ uint32_t prmt(uint32_t a, uint32_t b, uint32_t s) {
    uint32_t r; asm("prmt.b32 %0, %1, %2, %3;" : "=r"(r) : "r"(a), "r"(b), "r"(s)); return r;
}
__device__ __forceinline__ uint32_t pack_bf16(float lo, float hi) {
    uint32_t r; asm("cvt.rn.bf16x2.f32 %0, %1, %2;" : "=r"(r) : "f"(hi), "f"(lo)); return r;
}
__device__ __forceinline__ float bf16_round(float v) { return __uint_as_float(pack_bf16(0.f, v) & 0xffff0000u); }
__device__ __forceinline__ float ex2(float x) { float r; asm("ex2.approx.ftz.f32 %0, %1;" : "=f"(r) : "f"(x)); return r; }
__device__ __forceinline__ uint4 ld_rlx4(const void* p) {
    uint4 v;
    asm volatile("ld.relaxed.gpu.global.v4.u32 {%0,%1,%2,%3}, [%4];" : "=r"(v.x), "=r"(v.y), "=r"(v.z), "=r"(v.w) : "l"(p) : "memory");
    return v;
}
__device__ __forceinline__ uint32_t ld_acq(const void* p) {
    uint32_t v; asm volatile("ld.acquire.gpu.global.u32 %0, [%1];" : "=r"(v) : "l"(p) : "memory"); return v;
}
__device__ __forceinline__ void st_rlx(void* p, uint32_t v) { asm volatile("st.relaxed.gpu.global.u32 [%0], %1;" :: "l"(p), "r"(v) : "memory"); }
__device__ __forceinline__ void st_rlx4(void* p, uint32_t a, uint32_t b, uint32_t c, uint32_t d) {
    asm volatile("st.relaxed.gpu.global.v4.u32 [%0], {%1,%2,%3,%4};" :: "l"(p), "r"(a), "r"(b), "r"(c), "r"(d) : "memory");
}
__device__ __forceinline__ float warp_max(float v) {
    int k = __float_as_int(v);
    k ^= (k >> 31) & 0x7fffffff;
    k = __reduce_max_sync(0xffffffffu, k);
    k ^= (k >> 31) & 0x7fffffff;
    return __int_as_float(k);
}
__device__ __forceinline__ uint32_t tagf(float v, uint32_t par) { return (__float_as_uint(v) & ~1u) | par; }
__device__ __forceinline__ void wait_count(const uint32_t* c, uint32_t val, uint32_t sleep) {
#pragma unroll 1
    for (uint32_t it = 0; it < SPIN_LIMIT && ld_acq(c) != val; it++) __nanosleep(sleep);
}
__device__ __forceinline__ uint32_t take_ticket(uint32_t* c) {
    uint32_t v; asm volatile("atom.relaxed.gpu.global.add.u32 %0, [%1], 1;" : "=r"(v) : "l"(c) : "memory"); return v;
}
__device__ __forceinline__ void add_rel(uint32_t* c) { asm volatile("red.release.gpu.global.add.u32 [%0], 1;" :: "l"(c) : "memory"); }
__device__ __forceinline__ uint32_t tag16(uint32_t ep) { return (ep & 0x7fffu) | 0x8000u; }
__device__ __forceinline__ void gather128(const uint32_t* src, uint32_t tag, unsigned char* dst, int lane, uint32_t sleep) {
    uint4 v;
#pragma unroll 1
    for (uint32_t it = 0; it < SPIN_LIMIT; it++) {
        v = ld_rlx4(src + lane * 4);
        const bool ok = ((((v.x ^ tag) | (v.y ^ tag)) | ((v.z ^ tag) | (v.w ^ tag))) & 0xffffu) == 0;
        if (__all_sync(0xffffffffu, ok)) break;
        __nanosleep(sleep);
    }
    *reinterpret_cast<uint2*>(dst + lane * 8) = make_uint2(prmt(v.x, v.y, 0x7632), prmt(v.z, v.w, 0x7632));
}

__device__ __forceinline__ void bulk_load_nh(uint32_t dst, const void* src, uint32_t bytes, uint32_t bar) {
    asm volatile("cp.async.bulk.shared::cluster.global.mbarrier::complete_tx::bytes [%0], [%1], %2, [%3];"
                 :: "r"(dst), "l"(src), "r"(bytes), "r"(bar) : "memory");
}
__device__ __forceinline__ void tma2d_hint(uint32_t dst, const CUtensorMap* tm, int c0, int c1, uint32_t bar, uint64_t pol) {
    asm volatile("cp.async.bulk.tensor.2d.shared::cluster.global.mbarrier::complete_tx::bytes.L2::cache_hint [%0], [%1, {%3, %4}], [%2], %5;"
                 :: "r"(dst), "l"(tm), "r"(bar), "r"(c0), "r"(c1), "l"(pol) : "memory");
}
__device__ __forceinline__ void tma3d_hint(uint32_t dst, const CUtensorMap* tm, int c0, int c1, int c2, uint32_t bar, uint64_t pol) {
    asm volatile("cp.async.bulk.tensor.3d.shared::cluster.global.mbarrier::complete_tx::bytes.L2::cache_hint [%0], [%1, {%3, %4, %5}], [%2], %6;"
                 :: "r"(dst), "l"(tm), "r"(bar), "r"(c0), "r"(c1), "r"(c2), "l"(pol) : "memory");
}
__device__ __forceinline__ void prefetch32(const void* p) { asm volatile("cp.async.bulk.prefetch.L2.global [%0], 32;" :: "l"(p) : "memory"); }
__device__ __forceinline__ void prefetch_tm(const CUtensorMap* tm) { asm volatile("prefetch.tensormap [%0];" :: "l"(tm) : "memory"); }
__device__ __forceinline__ int kperm(int d) { return (d & ~15) | ((d & 6) << 1) | ((d >> 2) & 2) | (d & 1); }

template <int NK>
__device__ __forceinline__ uint32_t load_wT(uint32_t (&w)[NK][4][4], uint32_t base, int lane) {
    const int r8 = lane & 7;
    const uint32_t a0 = base + (r8 + 8 * (lane >> 4)) * 128 + ((((lane >> 3) & 1) ^ r8) << 4);
    uint32_t dep = 0;
#pragma unroll
    for (int s = 0; s < NK; s++)
#pragma unroll
        for (int mt = 0; mt < 4; mt++) { ldsm4t(w[s][mt], (a0 ^ (mt << 5)) + s * 2048); dep |= w[s][mt][0]; }
    return dep;
}

__device__ __forceinline__ bool mbar_test(uint32_t bar, uint32_t parity) {
    uint32_t done;
    asm volatile("{\n.reg .pred p;\nmbarrier.test_wait.parity.shared::cta.b64 p, [%1], %2;\nselp.u32 %0, 1, 0, p;\n}"
                 : "=r"(done) : "r"(bar), "r"(parity) : "memory");
    return done;
}
__device__ __forceinline__ void st_rlx2x64(void* p, uint32_t a, uint32_t b, uint32_t c, uint32_t d) {
    asm volatile("{\n.reg .b64 u, v;\nmov.b64 u, {%1,%2};\nmov.b64 v, {%3,%4};\nst.relaxed.gpu.global.v2.b64 [%0], {u, v};\n}"
                 :: "l"(p), "r"(a), "r"(b), "r"(c), "r"(d) : "memory");
}
__device__ __forceinline__ void ld_rlx2x64_if(uint4& v, const void* p, uint32_t pred) {
    asm volatile("{\n.reg .pred p;\n.reg .b64 u, v;\nsetp.ne.u32 p, %5, 0;\nmov.b64 u, {%0,%1};\nmov.b64 v, {%2,%3};\n"
                 "@p ld.relaxed.gpu.global.v2.b64 {u, v}, [%4];\nmov.b64 {%0,%1}, u;\nmov.b64 {%2,%3}, v;\n}"
                 : "+r"(v.x), "+r"(v.y), "+r"(v.z), "+r"(v.w) : "l"(p), "r"(pred) : "memory");
}
__device__ __forceinline__ uint4 lds128(uint32_t a) {
    uint4 v; asm volatile("ld.shared.v4.u32 {%0,%1,%2,%3}, [%4];" : "=r"(v.x), "=r"(v.y), "=r"(v.z), "=r"(v.w) : "r"(a) : "memory"); return v;
}
__device__ __forceinline__ float lds32(uint32_t a) { float v; asm volatile("ld.shared.f32 %0, [%1];" : "=f"(v) : "r"(a) : "memory"); return v; }
__device__ __forceinline__ uint32_t untagged(const uint4& v, uint32_t par) {
    uint32_t bad;
    asm("lop3.b32 %0, %1, %2, %3, 0x7e;" : "=r"(bad) : "r"(v.x), "r"(v.z), "r"(par));
    return bad;
}
__device__ __forceinline__ uint32_t or3(uint32_t a, uint32_t b, uint32_t c) {
    uint32_t r; asm("lop3.b32 %0, %1, %2, %3, 0xfe;" : "=r"(r) : "r"(a), "r"(b), "r"(c)); return r;
}
__device__ __forceinline__ void red_bf2(void* p, uint32_t v, uint32_t pred) {
    asm volatile("{\n.reg .pred p;\nsetp.ne.u32 p, %2, 0;\n@p red.relaxed.gpu.global.add.noftz.bf16x2 [%0], %1;\n}" :: "l"(p), "r"(v), "r"(pred) : "memory");
}

__global__ void __launch_bounds__(NTHREADS, 1) fused_decode_kernel(const __grid_constant__ Hot H, const __grid_constant__ Params P) {
    extern __shared__ __align__(1024) unsigned char smem[];
    const uint32_t sb = (uint32_t)__cvta_generic_to_shared(smem);
    const int bid = blockIdx.x, h = bid >> 2, j = bid & 3;
    const int lane = threadIdx.x & 31;
    const int g = lane >> 2, t = lane & 3;
    const uint32_t bar_full = sb + OFF_BAR, bar_empty = bar_full + RING * 8;
    const uint32_t bar_xfull = bar_empty + RING * 8, bar_xempty = bar_xfull + 32, bar_vec = bar_xempty + 32, bar_trig = bar_vec + 16;
    const uint32_t bar_wo = bar_trig + 24, bar_cmb = bar_wo + 32, bar_ini = bar_cmb + 24, bar_gat = bar_ini + 8, bar_qreq = bar_gat + 64, bar_qfull = bar_qreq + 32;
    const uint32_t bar_mempty = bar_qfull + 32, bar_mfull = bar_mempty + 16;
    const uint32_t bar_sfull = bar_mfull + 16, bar_xdone = bar_sfull + 16;
    const int mat = bid & 1, cb = bid >> 1;
    const int ab = h & 3, asplit = h >> 2;
    const int br = j < 2, hp = h & 7, cbk = 2 * (h >> 3) + (j & 1);
    const int hl = br ? 24 + hp : 0;

    const char* kp = H.kp;
    const char* vp = H.vp;
    const uint64_t pol = policy_evict_first();
    if (threadIdx.x == 0) {
        mbar_init(bar_full, 1);
        asm volatile("fence.mbarrier_init.release.cluster;" ::: "memory");
        mbar_expect_tx(bar_full, CH_BYTES);
        bulk_load(sb + OFF_RING, kp + bid * CH_BYTES, CH_BYTES, bar_full, pol);
        TL(0); TLG(0);
#pragma unroll
        for (int i = 0; i < 4; i++) mbar_init(bar_xfull + i * 8, 1);
        mbar_init(bar_full + 8, 1);
        mbar_init(bar_ini, 1);
        asm volatile("fence.mbarrier_init.release.cluster;" ::: "memory");
#pragma unroll
        for (int i = 0; i < 4; i++) {
            mbar_expect_tx(bar_xfull + i * 8, CH_BYTES);
            tma2d_hint(sb + OFF_XR + i * CH_BYTES, &P.tm_wq[mat], 64 * cb, 128 * i, bar_xfull + i * 8, pol);
            if (i == 0) {
                mbar_expect_tx(bar_full + 8, CH_BYTES);
                bulk_load(sb + OFF_RING + CH_BYTES, vp + bid * CH_BYTES, CH_BYTES, bar_full + 8, pol);
                mbar_expect_tx(bar_ini, 4096 + 16);
                bulk_load_nh(sb + OFF_EP, &H.S->epoch[4 * h], 16, bar_ini);
                bulk_load_nh(sb + OFF_X, H.x[mat], 4096, bar_ini);
            }
        }
        *reinterpret_cast<int*>(smem + OFF_META) = bid;
#pragma unroll
        for (int i = 2; i < NBAR; i++)
            if ((i < 2 * RING || i >= 2 * RING + 4) && i != I_INI)
                mbar_init(bar_full + i * 8, ((i >= RING && i < 2 * RING) || (i >= NBAR - 5 && i < NBAR - 1)) ? 4
                                          : (i >= 2 * RING + 4 && i < 2 * RING + 10) ? 8 : i == NBAR - 1 ? 9 : 1);
        asm volatile("fence.mbarrier_init.release.cluster;" ::: "memory");
        mbar_arrive(bar_qreq);
    }

    __syncwarp();
    const int warp = __shfl_sync(0xffffffffu, threadIdx.x >> 5, 0);
    auto epoch = [&]() -> uint32_t {
        mbar_wait(bar_ini, 0);
        return __shfl_sync(0xffffffffu, reinterpret_cast<const uint32_t*>(smem + OFF_EP)[j], 0) + 1;
    };

    if (warp >= 12) {
        asm volatile("setmaxnreg.dec.sync.aligned.u32 40;");
        bar_sync(1, 512);
        const uint32_t ep = epoch();
        if (warp == 12) {
            if (lane == 0) {
                uint32_t* tick = &H.S->ticket[ep & 1][threadIdx.x & H.zero];
                if (bid == 0) H.S->ticket[(ep & 1) ^ 1][0] = 0;
                int ntrig = 0, piece = bid, i = 2;
                uint32_t next = 0, tclaim = 0;
#pragma unroll 1
                for (;; i++) {
                    const int s = i % RING;
                    if (i <= 4) mbar_wait<2048>(bar_xfull + (i - 2) * 8, 0);
                    if (i >= WIN) {
                        mbar_wait(bar_full + ((i - WIN) % RING) * 8, ((i - WIN) / RING) & 1);
                        if (i - WIN < 192) TL2(i - WIN);
                    }
                    if (i >= RING && !mbar_wait(bar_empty + s * 8, ((i / RING) - 1) & 1)) break;
                    if (!(i & 1)) {
                        piece = i == 2 ? NCTA + bid : 2 * NCTA + (int)next;
                        reinterpret_cast<volatile int*>(smem + OFF_META)[s >> 1] = piece < NPIECE ? piece : -1;
                        mbar_arrive(bar_qreq + (s >> 1) * 8);
                        while (ntrig < 3 && piece >= (ntrig == 0 ? TRIG0 : ntrig == 1 ? TRIG1 : TRIG2)) mbar_arrive(bar_trig + 8 * ntrig++);
                        if (piece >= NPIECE) break;
                    }
                    mbar_expect_tx(bar_full + s * 8, CH_BYTES);
                    bulk_load(sb + OFF_RING + s * CH_BYTES, ((i & 1) ? vp : kp) + (size_t)piece * CH_BYTES, CH_BYTES, bar_full + s * 8, pol);
                    if ((piece & 127) == 0 && piece + 2 * NCTA < NPIECE) prefetch32(((i & 1) ? vp : kp) + (size_t)(piece + 2 * NCTA) * CH_BYTES);
                    if ((piece >> 7) == 60) prefetch32(P.wo[br] + (hp + 16 * (i & 1)) * 65536 + 64 * cbk);
                    if (i & 1) {
                        if (hl >= HS && piece >= NPIECE - XS) {
                            tclaim += (NPIECE - piece) * DLR;
                            next = NPIECE - 2 * NCTA;
                        } else { next = take_ticket(tick); tclaim = clock(); }
                    }
                }
                const uint32_t tg = tclaim - (piece - NPIECE) * DLR;
                mbar_wait(bar_xdone, 0);
                if (i >= RING) mbar_wait(bar_empty + (i % RING) * 8 + 8, ((i / RING) - 1) & 1);
                const int tlook = TG - (31 - hl) * 64 * DLR;
                bool look = hl >= HS;
                auto since = [&]() -> int {
                    const int now = (int)((uint32_t)clock() - tg);
                    if (look && now >= tlook) { mbar_arrive(bar_cmb + 16); look = false; }
                    return now;
                };
#pragma unroll 1
                for (int k = 0; k < 4; k++) {
                    const uint32_t dst = sb + (k < 2 ? OFF_RING + (i % RING) * CH_BYTES : OFF_XR) + k * CH_BYTES;
                    const int wi = k - 2;
                    const uint32_t wb = wi >= 0 ? bar_wo + wi * 8 : bar_full + ((i + wi) % RING) * 8, wp = wi >= 0 ? 0 : ((i + wi) / RING) & 1;
                    while (wi >= 0 && hl < HS && since() < NB2 + wi * NBS) {}
                    while (!mbar_test(wb, wp) && since() < DL0 + k * DLS) {}
                    mbar_expect_tx(bar_wo + k * 8, CH_BYTES);
                    tma2d_hint(dst, &P.tm_wo[br], 64 * cbk, (hp + 8 * k) * 128, bar_wo + k * 8, pol);
                }
                while (look) since();
                TL(1);
            }
        } else if (warp == 15) {
            const uint32_t par = ep & 1;
            const uint32_t t0 = 64 * (32 * j + h + 1) + LAG, t1 = 64 * (96 + (hl < HURG ? hl : hl - 8) + 1) + LAG + LAG1, t2 = 64 * (96 + hl + 1) + LAG2;
            uint32_t fired = 0;
#pragma unroll 1
            for (int r = 0;; r++) {
                const unsigned char* mg = smem + OFF_MG + (r & 1) * MG_BYTES;
                if (!mbar_wait(bar_sfull + (r & 1) * 8, (r >> 1) & 1)) break;
                const uint32_t piece = *reinterpret_cast<const uint32_t*>(mg + 2048 + 144);
                if (piece < NPIECE) {
                    const float4 mw = *reinterpret_cast<const float4*>(mg + 2048 + 128);
                    const float mm = fmaxf(fmaxf(mw.x, mw.y), fmaxf(mw.z, mw.w));
                    const float e0 = ex2((mw.x - mm) * LOG2E), e1 = ex2((mw.y - mm) * LOG2E);
                    const float e2 = ex2((mw.z - mm) * LOG2E), e3 = ex2((mw.w - mm) * LOG2E);
                    float l = reinterpret_cast<const float*>(mg + 2048)[lane] * ((lane & 16) ? ((lane & 8) ? e3 : e2) : ((lane & 8) ? e1 : e0));
#pragma unroll
                    for (int o = 16; o > 0; o >>= 1) l += __shfl_xor_sync(0xffffffffu, l, o);
                    uint32_t* dst = &H.S->pB[piece][lane * 4];
                    if (piece >= NPIECE - 512) mbar_wait(bar_xdone, 0);
                    if (lane < 2) st_rlx2x64(&H.S->mlB[piece][lane * 4], tagf(l, par), __float_as_uint(mm), par, 0);
                    mbar_wait(bar_mfull + (r & 1) * 8, (r >> 1) & 1);
                    const float4 a = reinterpret_cast<const float4*>(mg)[lane],      b = reinterpret_cast<const float4*>(mg)[32 + lane];
                    const float4 c = reinterpret_cast<const float4*>(mg)[64 + lane], d = reinterpret_cast<const float4*>(mg)[96 + lane];
                    st_rlx2x64(dst, tagf((a.x * e0 + b.x * e1) + (c.x * e2 + d.x * e3), par), __float_as_uint((a.y * e0 + b.y * e1) + (c.y * e2 + d.y * e3)),
                                    tagf((a.z * e0 + b.z * e1) + (c.z * e2 + d.z * e3), par), __float_as_uint((a.w * e0 + b.w * e1) + (c.w * e2 + d.w * e3)));
                    TL3(3, 0);
                }
                __syncwarp();
                const uint32_t now = (piece >= t0 ? 1u : 0u) | (piece >= t1 ? 2u : 0u) | (piece >= t2 && hl < HS ? 4u : 0u);
                if (lane < 3 && ((now & ~fired) >> lane & 1)) mbar_arrive(bar_cmb + lane * 8);
                fired = now;
                if (piece >= NPIECE) break;
                if (lane == 0) mbar_arrive(bar_mempty + (r & 1) * 8);
            }
        } else if (warp == 14) {
            mbar_wait<2048>(bar_xfull + 24, 0);
            __nanosleep(QD0);
#pragma unroll 1
            for (int r = 0;; r++) {
                if (!mbar_wait(bar_qreq + (r & 3) * 8, (r >> 2) & 1)) break;
                const int piece = reinterpret_cast<volatile int*>(smem + OFF_META)[r & 3];
                if (piece >= 0) gather128(&H.S->q[0][piece >> 11][((piece >> 6) & 31) * 128], tag16(ep), smem + OFF_QT + (r & 3) * 256, lane, QD1);
                __syncwarp();
                if (lane == 0) mbar_arrive(bar_qfull + (r & 3) * 8);
                if (piece < 0) break;
            }
        } else if (warp == 13) {
            if (lane == 0) { prefetch_tm(&P.tm_wuk); prefetch_tm(j == 0 ? &P.tm_ckv : &P.tm_wuv); }
            int n = 4;
            auto acquire = [&](uint32_t bytes) -> uint32_t {
                mbar_wait(bar_xempty + (n & 3) * 8, ((n >> 2) - 1) & 1);
                mbar_expect_tx(bar_xfull + (n & 3) * 8, bytes);
                return (uint32_t)(n++ & 3);
            };
            if (lane == 0) {
#pragma unroll 1
                for (int k = 0; k < 2; k++) {
                    const uint32_t s = acquire(CH_BYTES);
                    tma2d_hint(sb + OFF_XR + s * CH_BYTES, &P.tm_wuk, h * 128 + 64 * k, 128 * j, bar_xfull + s * 8, pol);
                }
                if (j >= 2) {
                    mbar_wait(bar_trig, 0);
#pragma unroll 1
                    for (int k = 0; k < 4; k++) {
                        const uint32_t s = acquire(CH_BYTES);
                        tma2d_hint(sb + OFF_XR + s * CH_BYTES, &P.tm_wuv, h * 128 + 64 * (j - 2), 128 * k, bar_xfull + s * 8, pol);
                    }
                }
            }
            __syncwarp();
            if (j == 0) bar_sync(10, 64);
            if (lane == 0) {
                if (j == 0) wait_count(H.S->cntQ, ep * NCTA, QSLEEP);
                else if (j >= 2) { mbar_wait(bar_trig + 8, 0); wait_count(H.S->cntA, ep * 4 * A_SPLITS, FSLEEP); }
                asm volatile("fence.proxy.async.global;" ::: "memory");
                if (j == 0) {
#pragma unroll 1
                    for (int k = 0; k < 4; k++) {
                        const uint32_t s = acquire(CH_BYTES);
                        bulk_load_nh(sb + OFF_XR + s * CH_BYTES, &H.S->qabs[ab][2 * k][0][0][0][0][0], CH_BYTES, bar_xfull + s * 8);
                    }
#pragma unroll 1
                    for (int k = 0; k < A_TILES; k++) {
                        const uint32_t s = acquire(CH_BYTES);
                        tma3d_hint(sb + OFF_XR + s * CH_BYTES, &P.tm_ckv, 0, ab * 4096 + 16 * (k * A_SPLITS + asplit), 0, bar_xfull + s * 8, pol);
                    }
                } else if (j >= 2) {
#pragma unroll 1
                    for (int k = 0; k < 4; k++) {
                        const uint32_t s = acquire(CH_BYTES + A_SPLITS * 8);
                        bulk_load_nh(sb + OFF_XR + s * CH_BYTES, &H.S->pA[h][k][0][0], CH_BYTES, bar_xfull + s * 8);
                        bulk_load_nh(sb + OFF_MLA + k * A_SPLITS * 8, &H.S->mlA[h][k][0], A_SPLITS * 8, bar_xfull + s * 8);
                    }
                }
            }
            __syncwarp();
            mbar_wait(bar_trig + 16, 0);
            if (lane == 0) {
                prefetch_tm(&P.tm_wo[br]);
                wait_count(H.S->cntQ, ep * NCTA, QSLEEP);
                mbar_arrive(bar_xdone);
            }
        }
    } else if (warp < 4) {
        asm volatile("setmaxnreg.dec.sync.aligned.u32 88;");
        bar_sync(1, 512);
        const uint32_t ep = epoch();
        const bool valid = (t == (g >> 1));
        const bool odd = g & 1;
        const int r8 = lane & 7;
        const uint32_t koff = (warp * 16 + r8 + 8 * ((lane >> 3) & 1)) * 256 + (((lane >> 4) ^ r8) << 4);
        const uint32_t voff = (warp * 16 + r8 + 8 * (lane >> 4)) * 256 + ((((lane >> 3) & 1) ^ r8) << 4);
        int r = 0;
#pragma unroll 1
        for (;; r++) {
            const int sk = (2 * r) % RING, sv = sk + 1;
            const uint32_t ph = ((2 * r) / RING) & 1;
            unsigned char* mg = smem + OFF_MG + (r & 1) * MG_BYTES;
            if (!mbar_wait(bar_qfull + (r & 3) * 8, ph)) break;
            if (r == 0 && threadIdx.x == 0) TL(4);
            const int piece = reinterpret_cast<volatile int*>(smem + OFF_META)[r & 3];
            if (piece < 0) {
                mbar_wait(bar_mempty + (r & 1) * 8, ((r >> 1) - 1) & 1);
                if (lane == 0) { *reinterpret_cast<int*>(mg + 2048 + 144) = piece; mbar_arrive(bar_sfull + (r & 1) * 8); }
                break;
            }
            uint32_t qf[16];
#pragma unroll
            for (int u = 0; u < 16; u++) qf[u] = reinterpret_cast<const uint32_t*>(smem + OFF_QT + (r & 3) * 256)[4 * (u ^ g) + t];
            mbar_wait(bar_full + sk * 8, ph);
            const uint32_t ka = sb + OFF_RING + sk * CH_BYTES + koff;
            float c0[4] = {0.f, 0.f, 0.f, 0.f}, c1[4] = {0.f, 0.f, 0.f, 0.f};
#pragma unroll
            for (int s = 0; s < 8; s += 2) {
                uint32_t a[4], b[4];
                ldsm4(a, ka ^ (s << 5));
                ldsm4(b, ka ^ ((s + 1) << 5));
                mma(c0, a[0], a[1], a[2], a[3], qf[2 * s], qf[2 * s + 1]);
                mma(c1, b[0], b[1], b[2], b[3], qf[2 * s + 2], qf[2 * s + 3]);
            }
            float slo = odd ? c0[1] + c1[1] : c0[0] + c1[0];
            float shi = odd ? c0[3] + c1[3] : c0[2] + c1[2];
            if (lane == 0) mbar_arrive(bar_empty + sk * 8 + (__float_as_uint(slo) & H.zero));
            slo = bf16_round(bf16_round(slo) * SCALE);
            shi = bf16_round(bf16_round(shi) * SCALE);
            const float m = warp_max(valid ? fmaxf(slo, shi) : -INFINITY);
            const float plo = valid ? ex2((slo - m) * LOG2E) : 0.f;
            const float phi = valid ? ex2((shi - m) * LOG2E) : 0.f;
            if (r >= 2) mbar_wait(bar_mempty + (r & 1) * 8, ((r >> 1) - 1) & 1);
            if (valid) reinterpret_cast<float*>(mg + 2048)[warp * 8 + g] = plo + phi;
            if (lane == 0) { reinterpret_cast<float*>(mg + 2048 + 128)[warp] = m; *reinterpret_cast<int*>(mg + 2048 + 144) = piece; }
            __syncwarp();
            if (lane == 0) mbar_arrive(bar_sfull + (r & 1) * 8);
            const uint32_t b0 = odd ? pack_bf16(0.f, plo) : pack_bf16(plo, 0.f);
            const uint32_t b1 = odd ? pack_bf16(0.f, phi) : pack_bf16(phi, 0.f);
            mbar_wait(bar_full + sv * 8, ph);
            if (warp == 0) TL3(0, 0);
            const uint32_t va = sb + OFF_RING + sv * CH_BYTES + voff;
            float ev[8], od[8];
#pragma unroll
            for (int i = 0; i < 8; i++) {
                uint32_t a[4];
                float acc[4] = {0.f, 0.f, 0.f, 0.f};
                ldsm4t(a, va ^ (i << 5));
                mma(acc, a[0], a[1], a[2], a[3], b0, b1);
                ev[i] = acc[0] + acc[3]; od[i] = acc[1] + acc[2];
            }
#pragma unroll
            for (int i = 0; i < 8; i += 2) {
                ev[i] += __shfl_xor_sync(0xffffffffu, ev[i + 1], 1);
                od[i] += __shfl_xor_sync(0xffffffffu, od[i + 1], 1);
            }
#pragma unroll
            for (int i = 0; i < 8; i += 4) {
                ev[i] += __shfl_xor_sync(0xffffffffu, ev[i + 2], 2);
                od[i] += __shfl_xor_sync(0xffffffffu, od[i + 2], 2);
            }
            reinterpret_cast<float4*>(mg)[warp * 32 + lane] = make_float4(ev[0], od[0], ev[4], od[4]);
            __syncwarp();
            if (lane == 0) {
                mbar_arrive(bar_mfull + (r & 1) * 8);
                mbar_arrive(bar_empty + sv * 8 + ((__float_as_uint(ev[0]) | __float_as_uint(ev[4])) & H.zero));
            }
        }
        TL3(2, 0);
        {
            int lane2 = lane;
            asm volatile("" : "+r"(lane2));
            const int g2 = lane2 >> 2;
            uint16_t* outp = reinterpret_cast<uint16_t*>(P.out) + (2 * (lane2 & 1) + ((lane2 >> 1) & 1)) * 1024 + 512 * br + 64 * cbk + 16 * warp + ((g2 & 1) ? g2 + 7 : g2);
            const uint32_t aoff = (r8 + 8 * (lane2 >> 4)) * 128 + (((2 * warp + ((lane2 >> 3) & 1)) ^ r8) << 4);
            uint32_t a0 = sb + OFF_RING + ((2 * r) % RING) * CH_BYTES + aoff;
            uint32_t vp0 = sb + OFF_SS + (g2 & 3) * 288 + 8 * (lane2 & 3);
            float d[2][4];
#pragma unroll
            for (int u = 0; u < 2; u++) d[u][0] = d[u][1] = d[u][2] = d[u][3] = 0.f;
#pragma unroll 1
            for (int k = 0; k < 4; k++) {
                uint32_t wf[8][4];
                uint2 ob[8];
                const uint32_t vb = bar_vec + (k == 3 ? 8 : 0), wb = bar_wo + k * 8;
                auto load_w = [&]() {
#pragma unroll
                    for (int s = 0; s < 8; s++) ldsm4t(wf[s], a0 + s * 2048);
                };
                auto load_v = [&]() {
#pragma unroll
                    for (int s = 0; s < 8; s++)
                        asm volatile("ld.shared.v2.u32 {%0,%1}, [%2];" : "=r"(ob[s].x), "=r"(ob[s].y) : "r"(vp0 + 32 * s) : "memory");
                };
                auto mmas = [&]() {
#pragma unroll
                    for (int s = 0; s < 8; s++) mma(d[s & 1], wf[s][0], wf[s][1], wf[s][2], wf[s][3], ob[s].x, ob[s].y);
                };
                bool vfirst = false;
                if (k) {
#pragma unroll 1
                    for (uint32_t it = 0; it < SPIN_LIMIT * 16; it++) {
                        vfirst = mbar_test(vb, 0);
                        if (vfirst || mbar_test(wb, 0)) break;
                    }
                }
                if (vfirst) {
                    load_v();
                    if (warp == 0) TL3(8 + k, 0);
                    mbar_wait(wb, 0);
                    if (warp == 0) TL3(20 + k, 0);
                    load_w(); mmas();
                } else {
                    mbar_wait(wb, 0);
                    if (warp == 0) TL3(20 + k, 0);
                    load_w();
                    mbar_wait(vb, 0);
                    if (warp == 0) TL3(8 + k, 0);
                    load_v(); mmas();
                }
                const float e0 = (t & 2) ? d[0][1] + d[1][1] : d[0][0] + d[1][0], e1 = (t & 2) ? d[0][3] + d[1][3] : d[0][2] + d[1][2];
                const float rv = __shfl_xor_sync(0xffffffffu, (g & 1) ? e0 : e1, 4);
                red_bf2(outp, (g & 1) ? pack_bf16(rv, e1) : pack_bf16(e0, rv), k == 3);
                a0 = k == 1 ? sb + OFF_XR + 2 * CH_BYTES + aoff : a0 + CH_BYTES;
                vp0 += 4 * 288;
            }
            TL3(12, 0);
        }
    } else {
        asm volatile("setmaxnreg.inc.sync.aligned.u32 192;");
        const int x = warp - 4, tid = threadIdx.x - 128;
        bar_sync(1, 512);
        const uint32_t ep = epoch();
        const uint32_t tag = tag16(ep), par = ep & 1;
        uint32_t* qdst = &H.S->q[mat][tid >> 6][mat ? kperm(64 * cb + (tid & 63)) : 64 * cb + (tid & 63)];
        st_rlx(qdst, 0);
        if (j >= 2) st_rlx(&H.S->vec[0][h][tid >> 6][kperm(64 * (j - 2) + (tid & 63))], 0);
        if (tid < 128) st_rlx(&H.S->vec[1][h][j][tid], 0);
        if (tid < 16) reinterpret_cast<uint32_t*>(P.out)[bid * 16 + tid] = 0u;
        if (!mat) {
            st_rlx4(&H.S->pB[NPIECE - 512 + 8 * cb + x][lane * 4], par ^ 1, par ^ 1, par ^ 1, par ^ 1);
            if (lane < 2) st_rlx4(&H.S->mlB[NPIECE - 512 + 8 * cb + x][lane * 4], par ^ 1, par ^ 1, par ^ 1, par ^ 1);
        }
        const uint32_t xr = sb + OFF_XR;
        auto xwait = [&](int n) { mbar_wait(bar_xfull + (n & 3) * 8, (n >> 2) & 1); };
        auto xrel  = [&](int n, uint32_t dep) { if (lane == 0) mbar_arrive(bar_xempty + (n & 3) * 8 + (dep & H.zero)); };
        float* red = reinterpret_cast<float*>(smem + OFF_SS + 8448);
        {
            uint32_t w[4][4][4], xb[4][2];
#pragma unroll
            for (int s = 0; s < 4; s++) {
                const uint32_t* X = reinterpret_cast<const uint32_t*>(smem + OFF_X) + (g & 3) * 256 + 32 * x + 8 * s + t;
                xb[s][0] = X[0]; xb[s][1] = X[4];
            }
            xwait(x >> 1);
            const uint32_t dep = load_wT<4>(w, xr + x * 8192, lane);
            float acc[4][4];
#pragma unroll
            for (int u = 0; u < 4; u++) acc[u][0] = acc[u][1] = acc[u][2] = acc[u][3] = 0.f;
#pragma unroll
            for (int s = 0; s < 4; s++)
#pragma unroll
                for (int mt = 0; mt < 4; mt++) mma(acc[mt], w[s][mt][0], w[s][mt][1], w[s][mt][2], w[s][mt][3], xb[s][0], xb[s][1]);
#pragma unroll
            for (int n = 0; n < 4; n++) xrel(n, dep);
            if (t < 2) {
#pragma unroll
                for (int mt = 0; mt < 4; mt++) {
                    float* r0 = red + (x * 4 + 2 * t) * 64 + 16 * mt + g;
                    r0[0] = acc[mt][0]; r0[8] = acc[mt][2]; r0[64] = acc[mt][1]; r0[72] = acc[mt][3];
                }
            }
            bar_sync(2, 256);
            float s = 0.f;
#pragma unroll
            for (int i = 0; i < 8; i++) s += red[i * 256 + tid];
            st_rlx(qdst, (pack_bf16(0.f, s) & 0xffff0000u) | tag);
        }
        if (tid == 0) TL(6);
        {
            uint32_t w[8][4];
            const int r8 = lane & 7;
            const uint32_t a0 = xr + (16 * x + r8 + 8 * ((lane >> 3) & 1)) * 128 + (((lane >> 4) ^ r8) << 4);
#pragma unroll
            for (int hf = 0; hf < 2; hf++) {
                xwait(4 + hf);
                uint32_t dep = 0;
#pragma unroll
                for (int ks = 0; ks < 4; ks++) { ldsm4(w[4 * hf + ks], (a0 ^ (ks << 5)) + hf * CH_BYTES); dep |= w[4 * hf + ks][0]; }
                xrel(4 + hf, dep);
            }
            if (x < 4) gather128(&H.S->q[1][x][h * 128], tag, smem + OFF_OA + x * 288, lane, QD1);
            bar_sync(2, 256);
            float c[4] = {0.f, 0.f, 0.f, 0.f};
#pragma unroll
            for (int i = 0; i < 8; i++) {
                const uint2 b = *reinterpret_cast<const uint2*>(smem + OFF_OA + (g & 3) * 288 + (16 * i + 4 * t) * 2);
                mma(c, w[i][0], w[i][1], w[i][2], w[i][3], b.x, b.y);
            }
            uint16_t* stg = reinterpret_cast<uint16_t*>(smem + OFF_SS);
            if (t < 2) {
                const int ks = x & 3;
#pragma unroll
                for (int q = 0; q < 4; q++) {
                    const int b = 2 * t + (q & 1), rg = q >> 1;
                    const float vh = bf16_round(c[q]);
                    const int o = b * 256 + (x >> 2) * 128 + (ks >> 1) * 32 + (g >> 1) * 8 + (ks & 1) * 4 + rg * 2 + (g & 1);
                    stg[o]      = (uint16_t)(__float_as_uint(vh) >> 16);
                    stg[o + 64] = (uint16_t)pack_bf16(c[q] - vh, 0.f);
                }
            }
            bar_sync(2, 256);
            if (tid < 128) {
                const uint4 val = reinterpret_cast<const uint4*>(stg)[tid];
                *reinterpret_cast<uint4*>(&H.S->qabs[tid >> 5][2 * j + ((tid >> 4) & 1)][(tid >> 3) & 1][h >> 3][(tid >> 2) & 1][(h & 7) * 4 + (tid & 3)][0]) = val;
            }
            bar_sync(2, 256);
            if (tid == 0) { add_rel(H.S->cntQ); TL(7); }
            if (j == 0 && x == 0) bar_arrive(10, 64);
        }
        if (j == 0) {
            uint32_t qf[2][4][8];
#pragma unroll
            for (int k = 0; k < 4; k++) {
                xwait(6 + k);
                uint32_t dep = 0;
                if (k == (x >> 1)) {
                    const unsigned char* qp = smem + OFF_XR + ((6 + k) & 3) * CH_BYTES + (x & 1) * 8192 + lane * 16;
#pragma unroll
                    for (int i = 0; i < 16; i++) {
                        const uint4 a = *reinterpret_cast<const uint4*>(qp + i * 512);
                        uint32_t* d = &qf[i >> 3][(i >> 1) & 3][4 * (i & 1)];
                        d[0] = a.x; d[1] = a.y; d[2] = a.z; d[3] = a.w;
                        dep |= a.x;
                    }
                }
                xrel(6 + k, dep);
            }
            if (tid == 0) TL(8);
            float acc[4][4][4];
#pragma unroll
            for (int a = 0; a < 4; a++)
#pragma unroll
                for (int b = 0; b < 4; b++) acc[a][b][0] = acc[a][b][1] = acc[a][b][2] = acc[a][b][3] = 0.f;
            float m = -INFINITY, l = 0.f;
            const int r8 = lane & 7;
            const uint32_t koff = x * 2048 + (r8 + 8 * ((lane >> 3) & 1)) * 128 + (((lane >> 4) ^ r8) << 4);
            const uint32_t voff = x * 2048 + (r8 + 8 * (lane >> 4)) * 128 + ((((lane >> 3) & 1) ^ r8) << 4);
            const int sh = tid >> 3, skp = tid & 7;
#define CK0
#define CK1(v)
            for (int n = 10; n < 10 + A_TILES; n++) {
                CK0
                xwait(n);
                CK1(cw)
                const uint32_t base = xr + (n & 3) * CH_BYTES;
                float S[4][4];
#pragma unroll
                for (int nt = 0; nt < 4; nt++) S[nt][0] = S[nt][1] = S[nt][2] = S[nt][3] = 0.f;
#pragma unroll
                for (int ks = 0; ks < 4; ks++) {
                    uint32_t a[4];
                    ldsm4(a, base + (koff ^ (ks << 5)));
#pragma unroll
                    for (int nt = 0; nt < 4; nt++) mma(S[nt], a[0], a[1], a[2], a[3], qf[1][nt][2 * ks], qf[1][nt][2 * ks + 1]);
#pragma unroll
                    for (int nt = 0; nt < 4; nt++) mma(S[nt], a[0], a[1], a[2], a[3], qf[0][nt][2 * ks], qf[0][nt][2 * ks + 1]);
                }
#pragma unroll
                for (int nt = 0; nt < 4; nt++) {
                    unsigned char* sp = smem + OFF_SS + (x * 32 + 8 * nt + 2 * t) * 80 + 8 * g;
                    *reinterpret_cast<float2*>(sp) = make_float2(S[nt][0], S[nt][2]);
                    *reinterpret_cast<float2*>(sp + 80) = make_float2(S[nt][1], S[nt][3]);
                }
                bar_sync(2, 256);
                CK1(c1)
                float s0 = 0.f, s1 = 0.f;
#pragma unroll
                for (int w = 0; w < 8; w++) {
                    const float2 v = *reinterpret_cast<const float2*>(smem + OFF_SS + (w * 32 + sh) * 80 + 8 * skp);
                    s0 += v.x; s1 += v.y;
                }
                s0 = bf16_round(bf16_round(s0) * SCALE);
                s1 = bf16_round(bf16_round(s1) * SCALE);
                float mx = fmaxf(s0, s1);
                mx = fmaxf(mx, __shfl_xor_sync(0xffffffffu, mx, 1));
                mx = fmaxf(mx, __shfl_xor_sync(0xffffffffu, mx, 2));
                mx = fmaxf(mx, __shfl_xor_sync(0xffffffffu, mx, 4));
                mx = fmaxf(mx, m);
                const float al = ex2((m - mx) * LOG2E);
                m = mx;
                const float p0 = ex2((s0 - m) * LOG2E), p1 = ex2((s1 - m) * LOG2E);
                l = l * al + p0 + p1;
                {
                    const uint32_t pp = pack_bf16(p0, p1);
                    uint16_t* dst = reinterpret_cast<uint16_t*>(smem + OFF_SP) + sh * 16 + kperm(skp);
                    dst[0] = (uint16_t)pp; dst[2] = (uint16_t)(pp >> 16);
                }
                if (skp == 0) reinterpret_cast<float*>(smem + OFF_ALPHA)[sh] = al;
                bar_sync(2, 256);
                CK1(c2)
                uint2 pb[4];
#pragma unroll
                for (int nt = 0; nt < 4; nt++) {
                    pb[nt] = *reinterpret_cast<const uint2*>(smem + OFF_SP + (8 * nt + g) * 32 + 8 * t);
                    const float2 a2 = *reinterpret_cast<const float2*>(smem + OFF_ALPHA + (8 * nt + 2 * t) * 4);
#pragma unroll
                    for (int mt = 0; mt < 4; mt++) {
                        acc[mt][nt][0] *= a2.x; acc[mt][nt][1] *= a2.y; acc[mt][nt][2] *= a2.x; acc[mt][nt][3] *= a2.y;
                    }
                }
                uint32_t dep = 0;
#pragma unroll
                for (int mt = 0; mt < 4; mt++) {
                    uint32_t a[4];
                    ldsm4t(a, base + (voff ^ (mt << 5)));
                    dep |= a[0];
#pragma unroll
                    for (int nt = 0; nt < 4; nt++) mma(acc[mt][nt], a[0], a[1], a[2], a[3], pb[nt].x, pb[nt].y);
                }
                xrel(n, dep);
                CK1(c3)
            }
#pragma unroll
            for (int nt = 0; nt < 4; nt++)
#pragma unroll
                for (int e = 0; e < 2; e++) {
                    float* dst = &H.S->pA[8 * nt + 2 * t + e][ab][asplit][64 * x + 4 * g];
                    *reinterpret_cast<float4*>(dst)      = make_float4(acc[0][nt][e], acc[0][nt][2 + e], acc[1][nt][e], acc[1][nt][2 + e]);
                    *reinterpret_cast<float4*>(dst + 32) = make_float4(acc[2][nt][e], acc[2][nt][2 + e], acc[3][nt][e], acc[3][nt][2 + e]);
                }
            l += __shfl_xor_sync(0xffffffffu, l, 1);
            l += __shfl_xor_sync(0xffffffffu, l, 2);
            l += __shfl_xor_sync(0xffffffffu, l, 4);
            if (skp == 0) H.S->mlA[sh][ab][asplit] = make_float2(m, l);
            bar_sync(2, 256);
            if (tid == 0) { add_rel(H.S->cntA); TL(9); }
        } else if (j >= 2) {
            uint32_t wv[4][4][4];
#pragma unroll
            for (int k = 0; k < 4; k++) {
                xwait(6 + k);
                uint32_t dep = 0;
                if (k == (x >> 1)) dep = load_wT<4>(wv, xr + ((6 + k) & 3) * CH_BYTES + (x & 1) * 8192, lane);
                xrel(6 + k, dep);
            }
            {
                const int b = tid >> 6, xx = (tid >> 3) & 7, gg = tid & 7;
                xwait(10 + b);
                if (tid == 0) TL(8);
                const float2* mlp = reinterpret_cast<const float2*>(smem + OFF_MLA) + b * A_SPLITS;
                float mm = -INFINITY, ll = 0.f;
#pragma unroll
                for (int s = 0; s < A_SPLITS; s++) mm = fmaxf(mm, mlp[s].x);
#pragma unroll
                for (int s = 0; s < A_SPLITS; s++) ll += mlp[s].y * ex2((mlp[s].x - mm) * LOG2E);
                const float inv = 1.f / ll;
                float cl[8];
#pragma unroll
                for (int e = 0; e < 8; e++) cl[e] = 0.f;
                const float* src = reinterpret_cast<const float*>(smem + OFF_XR + ((10 + b) & 3) * CH_BYTES) + 64 * xx + 4 * gg;
#pragma unroll
                for (int s = 0; s < A_SPLITS; s++) {
                    const float wt = ex2((mlp[s].x - mm) * LOG2E) * inv;
                    const float4 a = *reinterpret_cast<const float4*>(src + s * 512), c = *reinterpret_cast<const float4*>(src + s * 512 + 32);
                    cl[0] += wt * a.x; cl[1] += wt * a.y; cl[2] += wt * a.z; cl[3] += wt * a.w;
                    cl[4] += wt * c.x; cl[5] += wt * c.y; cl[6] += wt * c.z; cl[7] += wt * c.w;
                }
                uint16_t* hi = reinterpret_cast<uint16_t*>(smem + OFF_SS + b * 1056);
                uint16_t* lo = reinterpret_cast<uint16_t*>(smem + OFF_SS + (b + 4) * 1056);
#pragma unroll
                for (int e = 0; e < 8; e++) {
                    const int c = kperm(64 * xx + 8 * e + gg);
                    const float vh = bf16_round(cl[e]);
                    hi[c] = (uint16_t)(__float_as_uint(vh) >> 16);
                    lo[c] = (uint16_t)pack_bf16(cl[e] - vh, 0.f);
                }
                bar_sync(2, 256);
#pragma unroll
                for (int k = 0; k < 4; k++) xrel(10 + k, __float_as_uint(cl[0]) | __float_as_uint(cl[4]));
            }
            {
                float acc[4][4];
#pragma unroll
                for (int u = 0; u < 4; u++) acc[u][0] = acc[u][1] = acc[u][2] = acc[u][3] = 0.f;
#pragma unroll
                for (int s = 0; s < 4; s++) {
                    const uint2 b = *reinterpret_cast<const uint2*>(smem + OFF_SS + g * 1056 + (64 * x + 16 * s + 4 * t) * 2);
#pragma unroll
                    for (int mt = 0; mt < 4; mt++) mma(acc[mt], wv[s][mt][0], wv[s][mt][1], wv[s][mt][2], wv[s][mt][3], b.x, b.y);
                }
#pragma unroll
                for (int mt = 0; mt < 4; mt++)
#pragma unroll
                    for (int e = 0; e < 4; e++) acc[mt][e] += __shfl_xor_sync(0xffffffffu, acc[mt][e], 2);
                if (t < 2) {
#pragma unroll
                    for (int mt = 0; mt < 4; mt++) {
                        float* r0 = red + (x * 4 + 2 * t) * 64 + 16 * mt + g;
                        r0[0] = acc[mt][0]; r0[8] = acc[mt][2]; r0[64] = acc[mt][1]; r0[72] = acc[mt][3];
                    }
                }
            }
            bar_sync(2, 256);
            {
                float s = 0.f;
#pragma unroll
                for (int i = 0; i < 8; i++) s += red[i * 256 + tid];
                st_rlx(&H.S->vec[0][h][tid >> 6][kperm(64 * (j - 2) + (tid & 63))], (pack_bf16(0.f, s) & 0xffff0000u) | tag);
            }
            if (tid == 0) TL(9);
        }
        {
            __syncwarp();
            if (lane == 0) mbar_arrive(bar_xdone);
#pragma unroll 1
            for (uint32_t pass = H.zero; pass < 2; pass++) {
                if (pass == br) {
                    mbar_wait(br ? bar_cmb + 8 : bar_trig + 16, 0);
#pragma unroll 1
                    for (int u = 2 * x; u < 2 * x + 2; u++)
                        if (u < 15 || hl < HURG) gather128(&H.S->vec[br][hp + 8 * (u >> 2)][u & 3][0], tag, smem + OFF_SS + u * 288, lane, QD1);
                    __syncwarp();
                    if (lane == 0) { mbar_arrive(bar_vec); if (hl < HURG) mbar_arrive(bar_vec + 8); }
                    TL3(13, 0);
                    if (tid == 0) { H.S->epoch[bid] = ep; TL(10); }
                }
                if (pass ? hl >= HURG : (j < 3 || h < HURG)) {
                    const int pr = pass ? 96 + hl : 32 * j + h;
                    const uint32_t* rp = &H.S->pB[64 * pr + 8 * x][lane * 4];
                    const uint32_t* sp = &H.S->mlB[64 * pr + 8 * x + (lane & 7)][0];
                    uint4 v[8], sv;
                    mbar_wait(bar_cmb + pass * 16, 0);
                    TL3(5, 0);
                    if (lane == 0) {
                        mbar_expect_tx(bar_gat + x * 8, 4096 + 256);
                        bulk_load_nh(xr + x * 4096, rp, 4096, bar_gat + x * 8);
                        bulk_load_nh(sb + OFF_ST + x * 256, sp, 256, bar_gat + x * 8);
                    }
                    __syncwarp();
                    mbar_wait(bar_gat + x * 8, pass);
                    TL3(15, 0);
                    sv = lds128(sb + OFF_ST + x * 256 + (lane & 7) * 32);
#pragma unroll
                    for (int i = 0; i < 8; i++) v[i] = lds128(xr + x * 4096 + i * 512 + lane * 16);
                    float mx, ll, wt[8];
#pragma unroll 1
                    for (uint32_t it = 0;; it++) {
                        uint32_t bad[9];
#pragma unroll
                        for (int i = 0; i < 8; i++) bad[i] = untagged(v[i], par);
                        bad[8] = untagged(sv, par);
                        const uint32_t anyb = or3(or3(bad[0], bad[1], bad[2]), or3(bad[3], bad[4], bad[5]), or3(bad[6], bad[7], bad[8]));
                        const float m0 = __uint_as_float(sv.y);
                        mx = warp_max(m0);
                        const float w0 = ex2((m0 - mx) * LOG2E);
                        ll = w0 * __uint_as_float(sv.x);
                        const float l4 = __shfl_xor_sync(0xffffffffu, ll, 4);
#pragma unroll
                        for (int i = 0; i < 8; i++) wt[i] = __shfl_sync(0xffffffffu, w0, i);
                        ll += l4;
                        ll += __shfl_xor_sync(0xffffffffu, ll, 2);
                        if (!__any_sync(0xffffffffu, anyb & 1) || it >= SPIN_LIMIT) break;
                        uint32_t mask = 0;
#pragma unroll
                        for (int i = 0; i < 9; i++) mask |= (bad[i] & 1) << i;
                        const uint32_t pend = __reduce_or_sync(0xffffffffu, mask);
                        ld_rlx2x64_if(sv, sp, pend & 256);
#pragma unroll
                        for (int i = 0; i < 8; i++) ld_rlx2x64_if(v[i], rp + i * 128, pend & (1 << i));
                    }
                    ll += __shfl_xor_sync(0xffffffffu, ll, 1);
                    float4 acc = make_float4(0.f, 0.f, 0.f, 0.f), acd = acc;
#pragma unroll
                    for (int i = 0; i < 8; i += 2) {
                        acc.x += wt[i] * __uint_as_float(v[i].x); acc.y += wt[i] * __uint_as_float(v[i].y);
                        acc.z += wt[i] * __uint_as_float(v[i].z); acc.w += wt[i] * __uint_as_float(v[i].w);
                        acd.x += wt[i + 1] * __uint_as_float(v[i + 1].x); acd.y += wt[i + 1] * __uint_as_float(v[i + 1].y);
                        acd.z += wt[i + 1] * __uint_as_float(v[i + 1].z); acd.w += wt[i + 1] * __uint_as_float(v[i + 1].w);
                    }
                    acc.x += acd.x; acc.y += acd.y; acc.z += acd.z; acc.w += acd.w;
                    TL3(6, 0);
                    if (lane == 0) reinterpret_cast<float2*>(red + 1024)[x] = make_float2(mx, ll);
                    reinterpret_cast<float4*>(red)[tid] = acc;
                    const int d = kperm(16 * ((tid >> 2) & 3) + 8 * (tid & 1) + 64 * ((tid >> 1) & 1) + ((tid >> 4) & 7));
                    uint32_t od = sb + OFF_SS + 15 * 288 + 2 * d, ra = sb + OFF_SS + 8448;
                    asm volatile("" : "+r"(od), "+r"(ra));
                    bar_sync(2, 256);
                    if (x < 4) {
                        uint4 st[4];
                        float r[8];
#pragma unroll
                        for (int i = 0; i < 4; i++) st[i] = lds128(ra + 4096 + 16 * i);
#pragma unroll
                        for (int i = 0; i < 8; i++) r[i] = lds32(ra + 512 * i + 4 * tid);
                        float m2[4];
#pragma unroll
                        for (int i = 0; i < 4; i++) m2[i] = fmaxf(__uint_as_float(st[i].x), __uint_as_float(st[i].z));
                        const float mm = fmaxf(fmaxf(m2[0], m2[1]), fmaxf(m2[2], m2[3]));
                        float s0 = 0.f, s1 = 0.f, l0 = 0.f, l1 = 0.f;
#pragma unroll
                        for (int i = 0; i < 4; i++) {
                            const float f0 = ex2((__uint_as_float(st[i].x) - mm) * LOG2E), f1 = ex2((__uint_as_float(st[i].z) - mm) * LOG2E);
                            s0 += f0 * r[2 * i]; s1 += f1 * r[2 * i + 1];
                            l0 += f0 * __uint_as_float(st[i].y); l1 += f1 * __uint_as_float(st[i].w);
                        }
                        float inv;
                        asm("rcp.approx.ftz.f32 %0, %1;" : "=f"(inv) : "f"(l0 + l1));
                        const uint32_t ob = pack_bf16((s0 + s1) * inv, 0.f);
                        if (pass) asm volatile("st.shared.u16 [%0], %1;" :: "r"(od), "h"((uint16_t)ob) : "memory");
                        else st_rlx(&H.S->vec[1][h][j][d], (ob << 16) | tag);
                    }
                    __syncwarp();
                    if (pass && lane == 0) mbar_arrive(bar_vec + 8);
                    TL3(7, 0);
                    if (!pass) bar_sync(2, 256);
                }
            }
        }
    }
}

typedef CUresult (*EncodeFn)(CUtensorMap*, CUtensorMapDataType, cuuint32_t, void*, const cuuint64_t*, const cuuint64_t*,
                             const cuuint32_t*, const cuuint32_t*, CUtensorMapInterleave, CUtensorMapSwizzle,
                             CUtensorMapL2promotion, CUtensorMapFloatOOBfill);

void encode2d(EncodeFn fn, CUtensorMap* tm, void* ptr, uint64_t cols, uint64_t rows, uint32_t box_rows) {
    const cuuint64_t dims[2] = {cols, rows};
    const cuuint64_t strides[1] = {cols * 2};
    const cuuint32_t box[2] = {64, box_rows};
    const cuuint32_t es[2] = {1, 1};
    fn(tm, CU_TENSOR_MAP_DATA_TYPE_BFLOAT16, 2, ptr, dims, strides, box, es, CU_TENSOR_MAP_INTERLEAVE_NONE,
       CU_TENSOR_MAP_SWIZZLE_128B, CU_TENSOR_MAP_L2_PROMOTION_NONE, CU_TENSOR_MAP_FLOAT_OOB_FILL_NONE);
}

}

extern "C" void kernel_launch(void* const* d_in, const int* in_sizes, int n_in, void* d_out, int out_size) {
    (void)in_sizes; (void)n_in; (void)out_size;
    static EncodeFn encode = nullptr;
    static Scratch* scratch = nullptr;
    if (!encode) {
        cudaFuncSetAttribute(fused_decode_kernel, cudaFuncAttributeMaxDynamicSharedMemorySize, SMEM_BYTES + SMEM_EXTRA);
        void* fn = nullptr;
        cudaDriverEntryPointQueryResult qr;
        cudaGetDriverEntryPoint("cuTensorMapEncodeTiled", &fn, cudaEnableDefault, &qr);
        encode = (EncodeFn)fn;
        void* sp = nullptr;
        cudaGetSymbolAddress(&sp, g_scratch);
        scratch = (Scratch*)sp;
    }
    Params p;
    encode2d(encode, &p.tm_wq[0], d_in[9], 4096, 512, 128);
    encode2d(encode, &p.tm_wq[1], d_in[2], 4096, 512, 128);
    encode2d(encode, &p.tm_wuk,   d_in[3], 4096, 512, 128);
    encode2d(encode, &p.tm_wuv,   d_in[4], 4096, 512, 128);
    encode2d(encode, &p.tm_wo[1], d_in[10], 512, 4096, 128);
    encode2d(encode, &p.tm_wo[0], d_in[5], 512, 4096, 128);
    {
        const cuuint64_t dims[3] = {64, 16384, 8};
        const cuuint64_t strides[2] = {1024, 128};
        const cuuint32_t box[3] = {64, 16, 8};
        const cuuint32_t es[3] = {1, 1, 1};
        encode(&p.tm_ckv, CU_TENSOR_MAP_DATA_TYPE_BFLOAT16, 3, d_in[1], dims, strides, box, es, CU_TENSOR_MAP_INTERLEAVE_NONE,
               CU_TENSOR_MAP_SWIZZLE_128B, CU_TENSOR_MAP_L2_PROMOTION_NONE, CU_TENSOR_MAP_FLOAT_OOB_FILL_NONE);
    }
    p.wo[0] = (const __nv_bfloat16*)d_in[5];
    p.wo[1] = (const __nv_bfloat16*)d_in[10];
    p.out = (__nv_bfloat16*)d_out;
    Hot hp;
    hp.kp = (const char*)d_in[7];
    hp.vp = (const char*)d_in[8];
    hp.S = scratch;
    hp.x[0] = (const __nv_bfloat16*)d_in[6];
    hp.x[1] = (const __nv_bfloat16*)d_in[0];
    hp.zero = 0;
    cudaLaunchConfig_t cfg = {};
    cfg.gridDim = dim3(NCTA);
    cfg.blockDim = dim3(NTHREADS);
    cfg.dynamicSmemBytes = SMEM_BYTES + SMEM_EXTRA;
    cfg.stream = cudaStreamPerThread;
    cudaLaunchAttribute at[1];
    at[0].id = cudaLaunchAttributeCooperative;
    at[0].val.cooperative = 1;
    cfg.attrs = at;
    cfg.numAttrs = 1;
    cudaLaunchKernelEx(&cfg, fused_decode_kernel, hp, p);
}
```

```cpp
#include <cuda_runtime.h>
#include <cuda.h>
#include <cuda_bf16.h>
#include <stdint.h>

namespace {

constexpr int NCTA      = 128;
constexpr int NTHREADS  = 512;
constexpr int CH_BYTES  = 16384;
constexpr int NPIECE    = 128 * 64;
constexpr int RING      = 8;
#define WIN 3
#define DL0 3100
#define DLS 1000
#define NB2 4500
#define NBS 1300
#define DLR 18
#define DLQ 20
#define HS 31
#define XS 224
#define TG 5700
#define LAG 192
#define LAG2 96
#define LAG1 192
#define HURG 24
#define FSLEEP 600
#define QSLEEP 400
#define QD0 600
#define QD1 100
#define TRIG0 (20 * 128)
#define TRIG1 (32 * 128)
#define TRIG2 (50 * 128)
constexpr int SMEM_EXTRA = 0;
constexpr int A_SPLITS  = 8;
constexpr int A_TILES   = 4096 / A_SPLITS / 16;

constexpr int OFF_RING  = 0;
constexpr int OFF_XR    = OFF_RING + RING * CH_BYTES;
constexpr int OFF_SS    = OFF_XR + 4 * CH_BYTES;
constexpr int OFF_SP    = OFF_SS + 8 * 32 * 80;
constexpr int OFF_ALPHA = OFF_SP + 1024;
constexpr int OFF_OA    = OFF_ALPHA + 128;
constexpr int OFF_ST    = OFF_OA + 4 * 288;
constexpr int OFF_MLA   = OFF_ST + 64 * 32;
constexpr int OFF_QT    = OFF_MLA + 4 * A_SPLITS * 8;
constexpr int MG_BYTES  = 2048 + 128 + 32;
constexpr int OFF_MG    = OFF_QT + 4 * 256;
constexpr int OFF_META  = OFF_MG + 2 * MG_BYTES;
constexpr int OFF_EP    = OFF_META + 16;
constexpr int OFF_X     = OFF_SS + 4096;
constexpr int OFF_BAR   = OFF_EP + 16;
constexpr int NBAR      = 2 * RING + 8 + 2 + 3 + 4 + 3 + 1 + 8 + 8 + 2 + 2 + 2 + 1;
constexpr int I_INI     = 2 * RING + 8 + 2 + 3 + 4 + 3;
constexpr int SMEM_BYTES = OFF_BAR + NBAR * 8;

constexpr float LOG2E = 1.4426950408889634f;
constexpr float SCALE = 0.08838834764831845f;
constexpr uint32_t SPIN_LIMIT = 1u << 20;

struct Scratch {
    uint32_t ticket[2][64];
    uint32_t epoch[NCTA];
    uint32_t cntQ[64], cntA[64];
    float2   mlA[32][4][A_SPLITS];
    uint32_t vec[2][32][4][128];
    uint32_t q[2][4][4096];
    uint16_t qabs[4][8][2][4][2][32][8];
    float    pA[32][4][A_SPLITS][512];
    uint32_t pB[NPIECE][128];
    uint32_t mlB[NPIECE][8];
};
__device__ __align__(128) Scratch g_scratch;
#define TL(i) do {} while (0)
#define TL3(i, dep) do {} while (0)
#define TLG(i) do {} while (0)
#define TL2(i) do {} while (0)

struct Hot {
    const char *kp, *vp;
    Scratch* S;
    const __nv_bfloat16* x[2];
    uint32_t zero;
};
struct Params {
    CUtensorMap tm_wq[2];
    CUtensorMap tm_wuk, tm_wuv;
    CUtensorMap tm_wo[2];
    CUtensorMap tm_ckv;
    const __nv_bfloat16* wo[2];
    __nv_bfloat16* out;
};

__device__ __forceinline__ void mbar_init(uint32_t bar, uint32_t cnt) {
    asm volatile("mbarrier.init.shared::cta.b64 [%0], %1;" :: "r"(bar), "r"(cnt) : "memory");
}
__device__ __forceinline__ void mbar_expect_tx(uint32_t bar, uint32_t bytes) {
    asm volatile("mbarrier.arrive.expect_tx.shared::cta.b64 _, [%0], %1;" :: "r"(bar), "r"(bytes) : "memory");
}
__device__ __forceinline__ void mbar_arrive(uint32_t bar) {
    asm volatile("mbarrier.arrive.shared::cta.b64 _, [%0];" :: "r"(bar) : "memory");
}
template <uint32_t LIMIT = SPIN_LIMIT>
__device__ __forceinline__ bool mbar_wait(uint32_t bar, uint32_t parity) {
    uint32_t done, it = 0;
    do {
        asm volatile("{\n.reg .pred p;\nmbarrier.try_wait.parity.shared::cta.b64 p, [%1], %2;\nselp.u32 %0, 1, 0, p;\n}"
                     : "=r"(done) : "r"(bar), "r"(parity) : "memory");
        if (++it > LIMIT) break;
    } while (!done);
    return done;
}
__device__ __forceinline__ void bulk_load(uint32_t dst, const void* src, uint32_t bytes, uint32_t bar, uint64_t pol) {
    asm volatile("cp.async.bulk.shared::cluster.global.mbarrier::complete_tx::bytes.L2::cache_hint [%0], [%1], %2, [%3], %4;"
                 :: "r"(dst), "l"(src), "r"(bytes), "r"(bar), "l"(pol) : "memory");
}
__device__ __forceinline__ uint64_t policy_evict_first() {
    uint64_t pol;
    asm volatile("createpolicy.fractional.L2::evict_first.b64 %0, 1.0;" : "=l"(pol));
    return pol;
}
__device__ __forceinline__ void bar_sync(int id, int n)   { asm volatile("bar.sync %0, %1;" :: "r"(id), "r"(n) : "memory"); }
__device__ __forceinline__ void bar_arrive(int id, int n) { asm volatile("bar.arrive %0, %1;" :: "r"(id), "r"(n) : "memory"); }
__device__ __forceinline__ void ldsm4(uint32_t (&r)[4], uint32_t addr) {
    asm volatile("ldmatrix.sync.aligned.m8n8.x4.shared.b16 {%0,%1,%2,%3}, [%4];"
                 : "=r"(r[0]), "=r"(r[1]), "=r"(r[2]), "=r"(r[3]) : "r"(addr) : "memory");
}
__device__ __forceinline__ void ldsm4t(uint32_t (&r)[4], uint32_t addr) {
    asm volatile("ldmatrix.sync.aligned.m8n8.x4.trans.shared.b16 {%0,%1,%2,%3}, [%4];"
                 : "=r"(r[0]), "=r"(r[1]), "=r"(r[2]), "=r"(r[3]) : "r"(addr) : "memory");
}
__device__ __forceinline__ void mma(float (&c)[4], uint32_t a0, uint32_t a1, uint32_t a2, uint32_t a3, uint32_t b0, uint32_t b1) {
    asm volatile("mma.sync.aligned.m16n8k16.row.col.f32.bf16.bf16.f32 {%0,%1,%2,%3}, {%4,%5,%6,%7}, {%8,%9}, {%0,%1,%2,%3};"
                 : "+f"(c[0]), "+f"(c[1]), "+f"(c[2]), "+f"(c[3])
                 : "r"(a0), "r"(a1), "r"(a2), "r"(a3), "r"(b0), "r"(b1));
}
__device__ __forceinline__ uint32_t prmt(uint32_t a, uint32_t b, uint32_t s) {
    uint32_t r; asm("prmt.b32 %0, %1, %2, %3;" : "=r"(r) : "r"(a), "r"(b), "r"(s)); return r;
}
__device__ __forceinline__ uint32_t pack_bf16(float lo, float hi) {
    uint32_t r; asm("cvt.rn.bf16x2.f32 %0, %1, %2;" : "=r"(r) : "f"(hi), "f"(lo)); return r;
}
__device__ __forceinline__ float bf16_round(float v) { return __uint_as_float(pack_bf16(0.f, v) & 0xffff0000u); }
__device__ __forceinline__ float ex2(float x) { float r; asm("ex2.approx.ftz.f32 %0, %1;" : "=f"(r) : "f"(x)); return r; }
__device__ __forceinline__ uint4 ld_rlx4(const void* p) {
    uint4 v;
    asm volatile("ld.relaxed.gpu.global.v4.u32 {%0,%1,%2,%3}, [%4];" : "=r"(v.x), "=r"(v.y), "=r"(v.z), "=r"(v.w) : "l"(p) : "memory");
    return v;
}
__device__ __forceinline__ uint32_t ld_acq(const void* p) {
    uint32_t v; asm volatile("ld.acquire.gpu.global.u32 %0, [%1];" : "=r"(v) : "l"(p) : "memory"); return v;
}
__device__ __forceinline__ void st_rlx(void* p, uint32_t v) { asm volatile("st.relaxed.gpu.global.u32 [%0], %1;" :: "l"(p), "r"(v) : "memory"); }
__device__ __forceinline__ void st_rlx4(void* p, uint32_t a, uint32_t b, uint32_t c, uint32_t d) {
    asm volatile("st.relaxed.gpu.global.v4.u32 [%0], {%1,%2,%3,%4};" :: "l"(p), "r"(a), "r"(b), "r"(c), "r"(d) : "memory");
}
__device__ __forceinline__ float warp_max(float v) {
    int k = __float_as_int(v);
    k ^= (k >> 31) & 0x7fffffff;
    k = __reduce_max_sync(0xffffffffu, k);
    k ^= (k >> 31) & 0x7fffffff;
    return __int_as_float(k);
}
__device__ __forceinline__ uint32_t tagf(float v, uint32_t par) { return (__float_as_uint(v) & ~1u) | par; }
__device__ __forceinline__ void wait_count(const uint32_t* c, uint32_t val, uint32_t sleep) {
#pragma unroll 1
    for (uint32_t it = 0; it < SPIN_LIMIT && ld_acq(c) != val; it++) __nanosleep(sleep);
}
__device__ __forceinline__ uint32_t take_ticket(uint32_t* c) {
    uint32_t v; asm volatile("atom.relaxed.gpu.global.add.u32 %0, [%1], 1;" : "=r"(v) : "l"(c) : "memory"); return v;
}
__device__ __forceinline__ void add_rel(uint32_t* c) { asm volatile("red.release.gpu.global.add.u32 [%0], 1;" :: "l"(c) : "memory"); }
__device__ __forceinline__ uint32_t tag16(uint32_t ep) { return (ep & 0x7fffu) | 0x8000u; }
__device__ __forceinline__ void gather128(const uint32_t* src, uint32_t tag, unsigned char* dst, int lane, uint32_t sleep) {
    uint4 v;
#pragma unroll 1
    for (uint32_t it = 0; it < SPIN_LIMIT; it++) {
        v = ld_rlx4(src + lane * 4);
        const bool ok = ((((v.x ^ tag) | (v.y ^ tag)) | ((v.z ^ tag) | (v.w ^ tag))) & 0xffffu) == 0;
        if (__all_sync(0xffffffffu, ok)) break;
        __nanosleep(sleep);
    }
    *reinterpret_cast<uint2*>(dst + lane * 8) = make_uint2(prmt(v.x, v.y, 0x7632), prmt(v.z, v.w, 0x7632));
}

__device__ __forceinline__ void bulk_load_nh(uint32_t dst, const void* src, uint32_t bytes, uint32_t bar) {
    asm volatile("cp.async.bulk.shared::cluster.global.mbarrier::complete_tx::bytes [%0], [%1], %2, [%3];"
                 :: "r"(dst), "l"(src), "r"(bytes), "r"(bar) : "memory");
}
__device__ __forceinline__ void tma2d_hint(uint32_t dst, const CUtensorMap* tm, int c0, int c1, uint32_t bar, uint64_t pol) {
    asm volatile("cp.async.bulk.tensor.2d.shared::cluster.global.mbarrier::complete_tx::bytes.L2::cache_hint [%0], [%1, {%3, %4}], [%2], %5;"
                 :: "r"(dst), "l"(tm), "r"(bar), "r"(c0), "r"(c1), "l"(pol) : "memory");
}
__device__ __forceinline__ void tma3d_hint(uint32_t dst, const CUtensorMap* tm, int c0, int c1, int c2, uint32_t bar, uint64_t pol) {
    asm volatile("cp.async.bulk.tensor.3d.shared::cluster.global.mbarrier::complete_tx::bytes.L2::cache_hint [%0], [%1, {%3, %4, %5}], [%2], %6;"
                 :: "r"(dst), "l"(tm), "r"(bar), "r"(c0), "r"(c1), "r"(c2), "l"(pol) : "memory");
}
__device__ __forceinline__ void prefetch32(const void* p) { asm volatile("cp.async.bulk.prefetch.L2.global [%0], 32;" :: "l"(p) : "memory"); }
__device__ __forceinline__ void prefetch_tm(const CUtensorMap* tm) { asm volatile("prefetch.tensormap [%0];" :: "l"(tm) : "memory"); }
__device__ __forceinline__ int kperm(int d) { return (d & ~15) | ((d & 6) << 1) | ((d >> 2) & 2) | (d & 1); }

template <int NK>
__device__ __forceinline__ uint32_t load_wT(uint32_t (&w)[NK][4][4], uint32_t base, int lane) {
    const int r8 = lane & 7;
    const uint32_t a0 = base + (r8 + 8 * (lane >> 4)) * 128 + ((((lane >> 3) & 1) ^ r8) << 4);
    uint32_t dep = 0;
#pragma unroll
    for (int s = 0; s < NK; s++)
#pragma unroll
        for (int mt = 0; mt < 4; mt++) { ldsm4t(w[s][mt], (a0 ^ (mt << 5)) + s * 2048); dep |= w[s][mt][0]; }
    return dep;
}

__device__ __forceinline__ bool mbar_test(uint32_t bar, uint32_t parity) {
    uint32_t done;
    asm volatile("{\n.reg .pred p;\nmbarrier.test_wait.parity.shared::cta.b64 p, [%1], %2;\nselp.u32 %0, 1, 0, p;\n}"
                 : "=r"(done) : "r"(bar), "r"(parity) : "memory");
    return done;
}
__device__ __forceinline__ void st_rlx2x64(void* p, uint32_t a, uint32_t b, uint32_t c, uint32_t d) {
    asm volatile("{\n.reg .b64 u, v;\nmov.b64 u, {%1,%2};\nmov.b64 v, {%3,%4};\nst.relaxed.gpu.global.v2.b64 [%0], {u, v};\n}"
                 :: "l"(p), "r"(a), "r"(b), "r"(c), "r"(d) : "memory");
}
__device__ __forceinline__ void ld_rlx2x64_if(uint4& v, const void* p, uint32_t pred) {
    asm volatile("{\n.reg .pred p;\n.reg .b64 u, v;\nsetp.ne.u32 p, %5, 0;\nmov.b64 u, {%0,%1};\nmov.b64 v, {%2,%3};\n"
                 "@p ld.relaxed.gpu.global.v2.b64 {u, v}, [%4];\nmov.b64 {%0,%1}, u;\nmov.b64 {%2,%3}, v;\n}"
                 : "+r"(v.x), "+r"(v.y), "+r"(v.z), "+r"(v.w) : "l"(p), "r"(pred) : "memory");
}
__device__ __forceinline__ uint4 lds128(uint32_t a) {
    uint4 v; asm volatile("ld.shared.v4.u32 {%0,%1,%2,%3}, [%4];" : "=r"(v.x), "=r"(v.y), "=r"(v.z), "=r"(v.w) : "r"(a) : "memory"); return v;
}
__device__ __forceinline__ float lds32(uint32_t a) { float v; asm volatile("ld.shared.f32 %0, [%1];" : "=f"(v) : "r"(a) : "memory"); return v; }
__device__ __forceinline__ uint32_t untagged(const uint4& v, uint32_t par) {
    uint32_t bad;
    asm("lop3.b32 %0, %1, %2, %3, 0x7e;" : "=r"(bad) : "r"(v.x), "r"(v.z), "r"(par));
    return bad;
}
__device__ __forceinline__ uint32_t or3(uint32_t a, uint32_t b, uint32_t c) {
    uint32_t r; asm("lop3.b32 %0, %1, %2, %3, 0xfe;" : "=r"(r) : "r"(a), "r"(b), "r"(c)); return r;
}
__device__ __forceinline__ void red_bf2(void* p, uint32_t v, uint32_t pred) {
    asm volatile("{\n.reg .pred p;\nsetp.ne.u32 p, %2, 0;\n@p red.relaxed.gpu.global.add.noftz.bf16x2 [%0], %1;\n}" :: "l"(p), "r"(v), "r"(pred) : "memory");
}

__global__ void __launch_bounds__(NTHREADS, 1) fused_decode_kernel(const __grid_constant__ Hot H, const __grid_constant__ Params P) {
    extern __shared__ __align__(1024) unsigned char smem[];
    const uint32_t sb = (uint32_t)__cvta_generic_to_shared(smem);
    const int bid = blockIdx.x, h = bid >> 2, j = bid & 3;
    const int lane = threadIdx.x & 31;
    const int g = lane >> 2, t = lane & 3;
    const uint32_t bar_full = sb + OFF_BAR, bar_empty = bar_full + RING * 8;
    const uint32_t bar_xfull = bar_empty + RING * 8, bar_xempty = bar_xfull + 32, bar_vec = bar_xempty + 32, bar_trig = bar_vec + 16;
    const uint32_t bar_wo = bar_trig + 24, bar_cmb = bar_wo + 32, bar_ini = bar_cmb + 24, bar_gat = bar_ini + 8, bar_qreq = bar_gat + 64, bar_qfull = bar_qreq + 32;
    const uint32_t bar_mempty = bar_qfull + 32, bar_mfull = bar_mempty + 16;
    const uint32_t bar_sfull = bar_mfull + 16, bar_xdone = bar_sfull + 16;
    const int mat = bid & 1, cb = bid >> 1;
    const int ab = h & 3, asplit = h >> 2;
    const int br = j < 2, hp = h & 7, cbk = 2 * (h >> 3) + (j & 1);
    const int hl = br ? 24 + hp : 0;

    const char* kp = H.kp;
    const char* vp = H.vp;
    const uint64_t pol = policy_evict_first();
    if (threadIdx.x == 0) {
        mbar_init(bar_full, 1);
        asm volatile("fence.mbarrier_init.release.cluster;" ::: "memory");
        mbar_expect_tx(bar_full, CH_BYTES);
        bulk_load(sb + OFF_RING, kp + bid * CH_BYTES, CH_BYTES, bar_full, pol);
        TL(0); TLG(0);
#pragma unroll
        for (int i = 0; i < 4; i++) mbar_init(bar_xfull + i * 8, 1);
        mbar_init(bar_full + 8, 1);
        mbar_init(bar_ini, 1);
        asm volatile("fence.mbarrier_init.release.cluster;" ::: "memory");
#pragma unroll
        for (int i = 0; i < 4; i++) {
            mbar_expect_tx(bar_xfull + i * 8, CH_BYTES);
            tma2d_hint(sb + OFF_XR + i * CH_BYTES, &P.tm_wq[mat], 64 * cb, 128 * i, bar_xfull + i * 8, pol);
            if (i == 0) {
                mbar_expect_tx(bar_full + 8, CH_BYTES);
                bulk_load(sb + OFF_RING + CH_BYTES, vp + bid * CH_BYTES, CH_BYTES, bar_full + 8, pol);
                mbar_expect_tx(bar_ini, 4096 + 16);
                bulk_load_nh(sb + OFF_EP, &H.S->epoch[4 * h], 16, bar_ini);
                bulk_load_nh(sb + OFF_X, H.x[mat], 4096, bar_ini);
            }
        }
        *reinterpret_cast<int*>(smem + OFF_META) = bid;
#pragma unroll
        for (int i = 2; i < NBAR; i++)
            if ((i < 2 * RING || i >= 2 * RING + 4) && i != I_INI)
                mbar_init(bar_full + i * 8, ((i >= RING && i < 2 * RING) || (i >= NBAR - 5 && i < NBAR - 1)) ? 4
                                          : (i >= 2 * RING + 4 && i < 2 * RING + 10) ? 8 : i == NBAR - 1 ? 9 : 1);
        asm volatile("fence.mbarrier_init.release.cluster;" ::: "memory");
        mbar_arrive(bar_qreq);
    }

    __syncwarp();
    const int warp = __shfl_sync(0xffffffffu, threadIdx.x >> 5, 0);
    auto epoch = [&]() -> uint32_t {
        mbar_wait(bar_ini, 0);
        return __shfl_sync(0xffffffffu, reinterpret_cast<const uint32_t*>(smem + OFF_EP)[j], 0) + 1;
    };

    if (warp >= 12) {
        asm volatile("setmaxnreg.dec.sync.aligned.u32 40;");
        bar_sync(1, 512);
        const uint32_t ep = epoch();
        if (warp == 12) {
            if (lane == 0) {
                uint32_t* tick = &H.S->ticket[ep & 1][threadIdx.x & H.zero];
                if (bid == 0) H.S->ticket[(ep & 1) ^ 1][0] = 0;
                int ntrig = 0, piece = bid, i = 2;
                uint32_t next = 0, tclaim = 0;
#pragma unroll 1
                for (;; i++) {
                    const int s = i % RING;
                    if (i <= 4) mbar_wait<2048>(bar_xfull + (i - 2) * 8, 0);
                    if (i >= WIN) {
                        mbar_wait(bar_full + ((i - WIN) % RING) * 8, ((i - WIN) / RING) & 1);
                        if (i - WIN < 192) TL2(i - WIN);
                    }
                    if (i >= RING && !mbar_wait(bar_empty + s * 8, ((i / RING) - 1) & 1)) break;
                    if (!(i & 1)) {
                        piece = i == 2 ? NCTA + bid : 2 * NCTA + (int)next;
                        reinterpret_cast<volatile int*>(smem + OFF_META)[s >> 1] = piece < NPIECE ? piece : -1;
                        mbar_arrive(bar_qreq + (s >> 1) * 8);
                        while (ntrig < 3 && piece >= (ntrig == 0 ? TRIG0 : ntrig == 1 ? TRIG1 : TRIG2)) mbar_arrive(bar_trig + 8 * ntrig++);
                        if (piece >= NPIECE) break;
                    }
                    mbar_expect_tx(bar_full + s * 8, CH_BYTES);
                    bulk_load(sb + OFF_RING + s * CH_BYTES, ((i & 1) ? vp : kp) + (size_t)piece * CH_BYTES, CH_BYTES, bar_full + s * 8, pol);
                    if ((piece & 127) == 0 && piece + 2 * NCTA < NPIECE) prefetch32(((i & 1) ? vp : kp) + (size_t)(piece + 2 * NCTA) * CH_BYTES);
                    if ((piece >> 7) == 60) prefetch32(P.wo[br] + (hp + 16 * (i & 1)) * 65536 + 64 * cbk);
                    if (i & 1) {
                        if (hl >= HS && piece >= NPIECE - XS) {
                            tclaim += (NPIECE - piece) * DLR;
                            next = NPIECE - 2 * NCTA;
                        } else { next = take_ticket(tick); tclaim = clock(); }
                    }
                }
                const uint32_t tg = tclaim - (piece - NPIECE) * DLQ;
                mbar_wait(bar_xdone, 0);
                if (i >= RING) mbar_wait(bar_empty + (i % RING) * 8 + 8, ((i / RING) - 1) & 1);
                const int tlook = TG - (31 - hl) * 64 * DLR;
                bool look = hl >= HS;
                auto since = [&]() -> int {
                    const int now = (int)((uint32_t)clock() - tg);
                    if (look && now >= tlook) { mbar_arrive(bar_cmb + 16); look = false; }
                    return now;
                };
#pragma unroll 1
                for (int k = 0; k < 4; k++) {
                    const uint32_t dst = sb + (k < 2 ? OFF_RING + (i % RING) * CH_BYTES : OFF_XR) + k * CH_BYTES;
                    const int wi = k - 2;
                    const uint32_t wb = wi >= 0 ? bar_wo + wi * 8 : bar_full + ((i + wi) % RING) * 8, wp = wi >= 0 ? 0 : ((i + wi) / RING) & 1;
                    while (wi >= 0 && hl < HS && since() < NB2 + wi * NBS) {}
                    while (!mbar_test(wb, wp) && since() < DL0 + k * DLS) {}
                    mbar_expect_tx(bar_wo + k * 8, CH_BYTES);
                    tma2d_hint(dst, &P.tm_wo[br], 64 * cbk, (hp + 8 * k) * 128, bar_wo + k * 8, pol);
                }
                while (look) since();
                TL(1);
            }
        } else if (warp == 15) {
            const uint32_t par = ep & 1;
            const uint32_t t0 = 64 * (32 * j + h + 1) + LAG, t1 = 64 * (96 + (hl < HURG ? hl : hl - 8) + 1) + LAG + LAG1, t2 = 64 * (96 + hl + 1) + LAG2;
            uint32_t fired = 0;
#pragma unroll 1
            for (int r = 0;; r++) {
                const unsigned char* mg = smem + OFF_MG + (r & 1) * MG_BYTES;
                if (!mbar_wait(bar_sfull + (r & 1) * 8, (r >> 1) & 1)) break;
                const uint32_t piece = *reinterpret_cast<const uint32_t*>(mg + 2048 + 144);
                if (piece < NPIECE) {
                    const float4 mw = *reinterpret_cast<const float4*>(mg + 2048 + 128);
                    const float mm = fmaxf(fmaxf(mw.x, mw.y), fmaxf(mw.z, mw.w));
                    const float e0 = ex2((mw.x - mm) * LOG2E), e1 = ex2((mw.y - mm) * LOG2E);
                    const float e2 = ex2((mw.z - mm) * LOG2E), e3 = ex2((mw.w - mm) * LOG2E);
                    float l = reinterpret_cast<const float*>(mg + 2048)[lane] * ((lane & 16) ? ((lane & 8) ? e3 : e2) : ((lane & 8) ? e1 : e0));
#pragma unroll
                    for (int o = 16; o > 0; o >>= 1) l += __shfl_xor_sync(0xffffffffu, l, o);
                    uint32_t* dst = &H.S->pB[piece][lane * 4];
                    if (piece >= NPIECE - 512) mbar_wait(bar_xdone, 0);
                    if (lane < 2) st_rlx2x64(&H.S->mlB[piece][lane * 4], tagf(l, par), __float_as_uint(mm), par, 0);
                    mbar_wait(bar_mfull + (r & 1) * 8, (r >> 1) & 1);
                    const float4 a = reinterpret_cast<const float4*>(mg)[lane],      b = reinterpret_cast<const float4*>(mg)[32 + lane];
                    const float4 c = reinterpret_cast<const float4*>(mg)[64 + lane], d = reinterpret_cast<const float4*>(mg)[96 + lane];
                    st_rlx2x64(dst, tagf((a.x * e0 + b.x * e1) + (c.x * e2 + d.x * e3), par), __float_as_uint((a.y * e0 + b.y * e1) + (c.y * e2 + d.y * e3)),
                                    tagf((a.z * e0 + b.z * e1) + (c.z * e2 + d.z * e3), par), __float_as_uint((a.w * e0 + b.w * e1) + (c.w * e2 + d.w * e3)));
                    TL3(3, 0);
                }
                __syncwarp();
                const uint32_t now = (piece >= t0 ? 1u : 0u) | (piece >= t1 ? 2u : 0u) | (piece >= t2 && hl < HS ? 4u : 0u);
                if (lane < 3 && ((now & ~fired) >> lane & 1)) mbar_arrive(bar_cmb + lane * 8);
                fired = now;
                if (piece >= NPIECE) break;
                if (lane == 0) mbar_arrive(bar_mempty + (r & 1) * 8);
            }
        } else if (warp == 14) {
            mbar_wait<2048>(bar_xfull + 24, 0);
            __nanosleep(QD0);
#pragma unroll 1
            for (int r = 0;; r++) {
                if (!mbar_wait(bar_qreq + (r & 3) * 8, (r >> 2) & 1)) break;
                const int piece = reinterpret_cast<volatile int*>(smem + OFF_META)[r & 3];
                if (piece >= 0) gather128(&H.S->q[0][piece >> 11][((piece >> 6) & 31) * 128], tag16(ep), smem + OFF_QT + (r & 3) * 256, lane, QD1);
                __syncwarp();
                if (lane == 0) mbar_arrive(bar_qfull + (r & 3) * 8);
                if (piece < 0) break;
            }
        } else if (warp == 13) {
            if (lane == 0) { prefetch_tm(&P.tm_wuk); prefetch_tm(j == 0 ? &P.tm_ckv : &P.tm_wuv); }
            int n = 4;
            auto acquire = [&](uint32_t bytes) -> uint32_t {
                mbar_wait(bar_xempty + (n & 3) * 8, ((n >> 2) - 1) & 1);
                mbar_expect_tx(bar_xfull + (n & 3) * 8, bytes);
                return (uint32_t)(n++ & 3);
            };
            if (lane == 0) {
#pragma unroll 1
                for (int k = 0; k < 2; k++) {
                    const uint32_t s = acquire(CH_BYTES);
                    tma2d_hint(sb + OFF_XR + s * CH_BYTES, &P.tm_wuk, h * 128 + 64 * k, 128 * j, bar_xfull + s * 8, pol);
                }
                if (j >= 2) {
                    mbar_wait(bar_trig, 0);
#pragma unroll 1
                    for (int k = 0; k < 4; k++) {
                        const uint32_t s = acquire(CH_BYTES);
                        tma2d_hint(sb + OFF_XR + s * CH_BYTES, &P.tm_wuv, h * 128 + 64 * (j - 2), 128 * k, bar_xfull + s * 8, pol);
                    }
                }
            }
            __syncwarp();
            if (j == 0) bar_sync(10, 64);
            if (lane == 0) {
                if (j == 0) wait_count(H.S->cntQ, ep * NCTA, QSLEEP);
                else if (j >= 2) { mbar_wait(bar_trig + 8, 0); wait_count(H.S->cntA, ep * 4 * A_SPLITS, FSLEEP); }
                asm volatile("fence.proxy.async.global;" ::: "memory");
                if (j == 0) {
#pragma unroll 1
                    for (int k = 0; k < 4; k++) {
                        const uint32_t s = acquire(CH_BYTES);
                        bulk_load_nh(sb + OFF_XR + s * CH_BYTES, &H.S->qabs[ab][2 * k][0][0][0][0][0], CH_BYTES, bar_xfull + s * 8);
                    }
#pragma unroll 1
                    for (int k = 0; k < A_TILES; k++) {
                        const uint32_t s = acquire(CH_BYTES);
                        tma3d_hint(sb + OFF_XR + s * CH_BYTES, &P.tm_ckv, 0, ab * 4096 + 16 * (k * A_SPLITS + asplit), 0, bar_xfull + s * 8, pol);
                    }
                } else if (j >= 2) {
#pragma unroll 1
                    for (int k = 0; k < 4; k++) {
                        const uint32_t s = acquire(CH_BYTES + A_SPLITS * 8);
                        bulk_load_nh(sb + OFF_XR + s * CH_BYTES, &H.S->pA[h][k][0][0], CH_BYTES, bar_xfull + s * 8);
                        bulk_load_nh(sb + OFF_MLA + k * A_SPLITS * 8, &H.S->mlA[h][k][0], A_SPLITS * 8, bar_xfull + s * 8);
                    }
                }
            }
            __syncwarp();
            mbar_wait(bar_trig + 16, 0);
            if (lane == 0) {
                prefetch_tm(&P.tm_wo[br]);
                wait_count(H.S->cntQ, ep * NCTA, QSLEEP);
                mbar_arrive(bar_xdone);
            }
        }
    } else if (warp < 4) {
        asm volatile("setmaxnreg.dec.sync.aligned.u32 88;");
        bar_sync(1, 512);
        const uint32_t ep = epoch();
        const bool valid = (t == (g >> 1));
        const bool odd = g & 1;
        const int r8 = lane & 7;
        const uint32_t koff = (warp * 16 + r8 + 8 * ((lane >> 3) & 1)) * 256 + (((lane >> 4) ^ r8) << 4);
        const uint32_t voff = (warp * 16 + r8 + 8 * (lane >> 4)) * 256 + ((((lane >> 3) & 1) ^ r8) << 4);
        int r = 0;
#pragma unroll 1
        for (;; r++) {
            const int sk = (2 * r) % RING, sv = sk + 1;
            const uint32_t ph = ((2 * r) / RING) & 1;
            unsigned char* mg = smem + OFF_MG + (r & 1) * MG_BYTES;
            if (!mbar_wait(bar_qfull + (r & 3) * 8, ph)) break;
            if (r == 0 && threadIdx.x == 0) TL(4);
            const int piece = reinterpret_cast<volatile int*>(smem + OFF_META)[r & 3];
            if (piece < 0) {
                mbar_wait(bar_mempty + (r & 1) * 8, ((r >> 1) - 1) & 1);
                if (lane == 0) { *reinterpret_cast<int*>(mg + 2048 + 144) = piece; mbar_arrive(bar_sfull + (r & 1) * 8); }
                break;
            }
            uint32_t qf[16];
#pragma unroll
            for (int u = 0; u < 16; u++) qf[u] = reinterpret_cast<const uint32_t*>(smem + OFF_QT + (r & 3) * 256)[4 * (u ^ g) + t];
            mbar_wait(bar_full + sk * 8, ph);
            const uint32_t ka = sb + OFF_RING + sk * CH_BYTES + koff;
            float c0[4] = {0.f, 0.f, 0.f, 0.f}, c1[4] = {0.f, 0.f, 0.f, 0.f};
#pragma unroll
            for (int s = 0; s < 8; s += 2) {
                uint32_t a[4], b[4];
                ldsm4(a, ka ^ (s << 5));
                ldsm4(b, ka ^ ((s + 1) << 5));
                mma(c0, a[0], a[1], a[2], a[3], qf[2 * s], qf[2 * s + 1]);
                mma(c1, b[0], b[1], b[2], b[3], qf[2 * s + 2], qf[2 * s + 3]);
            }
            float slo = odd ? c0[1] + c1[1] : c0[0] + c1[0];
            float shi = odd ? c0[3] + c1[3] : c0[2] + c1[2];
            if (lane == 0) mbar_arrive(bar_empty + sk * 8 + (__float_as_uint(slo) & H.zero));
            slo = bf16_round(bf16_round(slo) * SCALE);
            shi = bf16_round(bf16_round(shi) * SCALE);
            const float m = warp_max(valid ? fmaxf(slo, shi) : -INFINITY);
            const float plo = valid ? ex2((slo - m) * LOG2E) : 0.f;
            const float phi = valid ? ex2((shi - m) * LOG2E) : 0.f;
            if (r >= 2) mbar_wait(bar_mempty + (r & 1) * 8, ((r >> 1) - 1) & 1);
            if (valid) reinterpret_cast<float*>(mg + 2048)[warp * 8 + g] = plo + phi;
            if (lane == 0) { reinterpret_cast<float*>(mg + 2048 + 128)[warp] = m; *reinterpret_cast<int*>(mg + 2048 + 144) = piece; }
            __syncwarp();
            if (lane == 0) mbar_arrive(bar_sfull + (r & 1) * 8);
            const uint32_t b0 = odd ? pack_bf16(0.f, plo) : pack_bf16(plo, 0.f);
            const uint32_t b1 = odd ? pack_bf16(0.f, phi) : pack_bf16(phi, 0.f);
            mbar_wait(bar_full + sv * 8, ph);
            if (warp == 0) TL3(0, 0);
            const uint32_t va = sb + OFF_RING + sv * CH_BYTES + voff;
            float ev[8], od[8];
#pragma unroll
            for (int i = 0; i < 8; i++) {
                uint32_t a[4];
                float acc[4] = {0.f, 0.f, 0.f, 0.f};
                ldsm4t(a, va ^ (i << 5));
                mma(acc, a[0], a[1], a[2], a[3], b0, b1);
                ev[i] = acc[0] + acc[3]; od[i] = acc[1] + acc[2];
            }
#pragma unroll
            for (int i = 0; i < 8; i += 2) {
                ev[i] += __shfl_xor_sync(0xffffffffu, ev[i + 1], 1);
                od[i] += __shfl_xor_sync(0xffffffffu, od[i + 1], 1);
            }
#pragma unroll
            for (int i = 0; i < 8; i += 4) {
                ev[i] += __shfl_xor_sync(0xffffffffu, ev[i + 2], 2);
                od[i] += __shfl_xor_sync(0xffffffffu, od[i + 2], 2);
            }
            reinterpret_cast<float4*>(mg)[warp * 32 + lane] = make_float4(ev[0], od[0], ev[4], od[4]);
            __syncwarp();
            if (lane == 0) {
                mbar_arrive(bar_mfull + (r & 1) * 8);
                mbar_arrive(bar_empty + sv * 8 + ((__float_as_uint(ev[0]) | __float_as_uint(ev[4])) & H.zero));
            }
        }
        TL3(2, 0);
        {
            int lane2 = lane;
            asm volatile("" : "+r"(lane2));
            const int g2 = lane2 >> 2;
            uint16_t* outp = reinterpret_cast<uint16_t*>(P.out) + (2 * (lane2 & 1) + ((lane2 >> 1) & 1)) * 1024 + 512 * br + 64 * cbk + 16 * warp + ((g2 & 1) ? g2 + 7 : g2);
            const uint32_t aoff = (r8 + 8 * (lane2 >> 4)) * 128 + (((2 * warp + ((lane2 >> 3) & 1)) ^ r8) << 4);
            uint32_t a0 = sb + OFF_RING + ((2 * r) % RING) * CH_BYTES + aoff;
            uint32_t vp0 = sb + OFF_SS + (g2 & 3) * 288 + 8 * (lane2 & 3);
            float d[2][4];
#pragma unroll
            for (int u = 0; u < 2; u++) d[u][0] = d[u][1] = d[u][2] = d[u][3] = 0.f;
#pragma unroll 1
            for (int k = 0; k < 4; k++) {
                uint32_t wf[8][4];
                uint2 ob[8];
                const uint32_t vb = bar_vec + (k == 3 ? 8 : 0), wb = bar_wo + k * 8;
                auto load_w = [&]() {
#pragma unroll
                    for (int s = 0; s < 8; s++) ldsm4t(wf[s], a0 + s * 2048);
                };
                auto load_v = [&]() {
#pragma unroll
                    for (int s = 0; s < 8; s++)
                        asm volatile("ld.shared.v2.u32 {%0,%1}, [%2];" : "=r"(ob[s].x), "=r"(ob[s].y) : "r"(vp0 + 32 * s) : "memory");
                };
                auto mmas = [&]() {
#pragma unroll
                    for (int s = 0; s < 8; s++) mma(d[s & 1], wf[s][0], wf[s][1], wf[s][2], wf[s][3], ob[s].x, ob[s].y);
                };
                bool vfirst = false;
                if (k) {
#pragma unroll 1
                    for (uint32_t it = 0; it < SPIN_LIMIT * 16; it++) {
                        vfirst = mbar_test(vb, 0);
                        if (vfirst || mbar_test(wb, 0)) break;
                    }
                }
                if (vfirst) {
                    load_v();
                    if (warp == 0) TL3(8 + k, 0);
                    mbar_wait(wb, 0);
                    if (warp == 0) TL3(20 + k, 0);
                    load_w(); mmas();
                } else {
                    mbar_wait(wb, 0);
                    if (warp == 0) TL3(20 + k, 0);
                    load_w();
                    mbar_wait(vb, 0);
                    if (warp == 0) TL3(8 + k, 0);
                    load_v(); mmas();
                }
                const float e0 = (t & 2) ? d[0][1] + d[1][1] : d[0][0] + d[1][0], e1 = (t & 2) ? d[0][3] + d[1][3] : d[0][2] + d[1][2];
                const float rv = __shfl_xor_sync(0xffffffffu, (g & 1) ? e0 : e1, 4);
                red_bf2(outp, (g & 1) ? pack_bf16(rv, e1) : pack_bf16(e0, rv), k == 3);
                a0 = k == 1 ? sb + OFF_XR + 2 * CH_BYTES + aoff : a0 + CH_BYTES;
                vp0 += 4 * 288;
            }
            TL3(12, 0);
        }
    } else {
        asm volatile("setmaxnreg.inc.sync.aligned.u32 192;");
        const int x = warp - 4, tid = threadIdx.x - 128;
        bar_sync(1, 512);
        const uint32_t ep = epoch();
        const uint32_t tag = tag16(ep), par = ep & 1;
        uint32_t* qdst = &H.S->q[mat][tid >> 6][mat ? kperm(64 * cb + (tid & 63)) : 64 * cb + (tid & 63)];
        st_rlx(qdst, 0);
        if (j >= 2) st_rlx(&H.S->vec[0][h][tid >> 6][kperm(64 * (j - 2) + (tid & 63))], 0);
        if (tid < 128) st_rlx(&H.S->vec[1][h][j][tid], 0);
        if (tid < 16) reinterpret_cast<uint32_t*>(P.out)[bid * 16 + tid] = 0u;
        if (!mat) {
            st_rlx4(&H.S->pB[NPIECE - 512 + 8 * cb + x][lane * 4], par ^ 1, par ^ 1, par ^ 1, par ^ 1);
            if (lane < 2) st_rlx4(&H.S->mlB[NPIECE - 512 + 8 * cb + x][lane * 4], par ^ 1, par ^ 1, par ^ 1, par ^ 1);
        }
        const uint32_t xr = sb + OFF_XR;
        auto xwait = [&](int n) { mbar_wait(bar_xfull + (n & 3) * 8, (n >> 2) & 1); };
        auto xrel  = [&](int n, uint32_t dep) { if (lane == 0) mbar_arrive(bar_xempty + (n & 3) * 8 + (dep & H.zero)); };
        float* red = reinterpret_cast<float*>(smem + OFF_SS + 8448);
        {
            uint32_t w[4][4][4], xb[4][2];
#pragma unroll
            for (int s = 0; s < 4; s++) {
                const uint32_t* X = reinterpret_cast<const uint32_t*>(smem + OFF_X) + (g & 3) * 256 + 32 * x + 8 * s + t;
                xb[s][0] = X[0]; xb[s][1] = X[4];
            }
            xwait(x >> 1);
            const uint32_t dep = load_wT<4>(w, xr + x * 8192, lane);
            float acc[4][4];
#pragma unroll
            for (int u = 0; u < 4; u++) acc[u][0] = acc[u][1] = acc[u][2] = acc[u][3] = 0.f;
#pragma unroll
            for (int s = 0; s < 4; s++)
#pragma unroll
                for (int mt = 0; mt < 4; mt++) mma(acc[mt], w[s][mt][0], w[s][mt][1], w[s][mt][2], w[s][mt][3], xb[s][0], xb[s][1]);
#pragma unroll
            for (int n = 0; n < 4; n++) xrel(n, dep);
            if (t < 2) {
#pragma unroll
                for (int mt = 0; mt < 4; mt++) {
                    float* r0 = red + (x * 4 + 2 * t) * 64 + 16 * mt + g;
                    r0[0] = acc[mt][0]; r0[8] = acc[mt][2]; r0[64] = acc[mt][1]; r0[72] = acc[mt][3];
                }
            }
            bar_sync(2, 256);
            float s = 0.f;
#pragma unroll
            for (int i = 0; i < 8; i++) s += red[i * 256 + tid];
            st_rlx(qdst, (pack_bf16(0.f, s) & 0xffff0000u) | tag);
        }
        if (tid == 0) TL(6);
        {
            uint32_t w[8][4];
            const int r8 = lane & 7;
            const uint32_t a0 = xr + (16 * x + r8 + 8 * ((lane >> 3) & 1)) * 128 + (((lane >> 4) ^ r8) << 4);
#pragma unroll
            for (int hf = 0; hf < 2; hf++) {
                xwait(4 + hf);
                uint32_t dep = 0;
#pragma unroll
                for (int ks = 0; ks < 4; ks++) { ldsm4(w[4 * hf + ks], (a0 ^ (ks << 5)) + hf * CH_BYTES); dep |= w[4 * hf + ks][0]; }
                xrel(4 + hf, dep);
            }
            if (x < 4) gather128(&H.S->q[1][x][h * 128], tag, smem + OFF_OA + x * 288, lane, QD1);
            bar_sync(2, 256);
            float c[4] = {0.f, 0.f, 0.f, 0.f};
#pragma unroll
            for (int i = 0; i < 8; i++) {
                const uint2 b = *reinterpret_cast<const uint2*>(smem + OFF_OA + (g & 3) * 288 + (16 * i + 4 * t) * 2);
                mma(c, w[i][0], w[i][1], w[i][2], w[i][3], b.x, b.y);
            }
            uint16_t* stg = reinterpret_cast<uint16_t*>(smem + OFF_SS);
            if (t < 2) {
                const int ks = x & 3;
#pragma unroll
                for (int q = 0; q < 4; q++) {
                    const int b = 2 * t + (q & 1), rg = q >> 1;
                    const float vh = bf16_round(c[q]);
                    const int o = b * 256 + (x >> 2) * 128 + (ks >> 1) * 32 + (g >> 1) * 8 + (ks & 1) * 4 + rg * 2 + (g & 1);
                    stg[o]      = (uint16_t)(__float_as_uint(vh) >> 16);
                    stg[o + 64] = (uint16_t)pack_bf16(c[q] - vh, 0.f);
                }
            }
            bar_sync(2, 256);
            if (tid < 128) {
                const uint4 val = reinterpret_cast<const uint4*>(stg)[tid];
                *reinterpret_cast<uint4*>(&H.S->qabs[tid >> 5][2 * j + ((tid >> 4) & 1)][(tid >> 3) & 1][h >> 3][(tid >> 2) & 1][(h & 7) * 4 + (tid & 3)][0]) = val;
            }
            bar_sync(2, 256);
            if (tid == 0) { add_rel(H.S->cntQ); TL(7); }
            if (j == 0 && x == 0) bar_arrive(10, 64);
        }
        if (j == 0) {
            uint32_t qf[2][4][8];
#pragma unroll
            for (int k = 0; k < 4; k++) {
                xwait(6 + k);
                uint32_t dep = 0;
                if (k == (x >> 1)) {
                    const unsigned char* qp = smem + OFF_XR + ((6 + k) & 3) * CH_BYTES + (x & 1) * 8192 + lane * 16;
#pragma unroll
                    for (int i = 0; i < 16; i++) {
                        const uint4 a = *reinterpret_cast<const uint4*>(qp + i * 512);
                        uint32_t* d = &qf[i >> 3][(i >> 1) & 3][4 * (i & 1)];
                        d[0] = a.x; d[1] = a.y; d[2] = a.z; d[3] = a.w;
                        dep |= a.x;
                    }
                }
                xrel(6 + k, dep);
            }
            if (tid == 0) TL(8);
            float acc[4][4][4];
#pragma unroll
            for (int a = 0; a < 4; a++)
#pragma unroll
                for (int b = 0; b < 4; b++) acc[a][b][0] = acc[a][b][1] = acc[a][b][2] = acc[a][b][3] = 0.f;
            float m = -INFINITY, l = 0.f;
            const int r8 = lane & 7;
            const uint32_t koff = x * 2048 + (r8 + 8 * ((lane >> 3) & 1)) * 128 + (((lane >> 4) ^ r8) << 4);
            const uint32_t voff = x * 2048 + (r8 + 8 * (lane >> 4)) * 128 + ((((lane >> 3) & 1) ^ r8) << 4);
            const int sh = tid >> 3, skp = tid & 7;
#define CK0
#define CK1(v)
            for (int n = 10; n < 10 + A_TILES; n++) {
                CK0
                xwait(n);
                CK1(cw)
                const uint32_t base = xr + (n & 3) * CH_BYTES;
                float S[4][4];
#pragma unroll
                for (int nt = 0; nt < 4; nt++) S[nt][0] = S[nt][1] = S[nt][2] = S[nt][3] = 0.f;
#pragma unroll
                for (int ks = 0; ks < 4; ks++) {
                    uint32_t a[4];
                    ldsm4(a, base + (koff ^ (ks << 5)));
#pragma unroll
                    for (int nt = 0; nt < 4; nt++) mma(S[nt], a[0], a[1], a[2], a[3], qf[1][nt][2 * ks], qf[1][nt][2 * ks + 1]);
#pragma unroll
                    for (int nt = 0; nt < 4; nt++) mma(S[nt], a[0], a[1], a[2], a[3], qf[0][nt][2 * ks], qf[0][nt][2 * ks + 1]);
                }
#pragma unroll
                for (int nt = 0; nt < 4; nt++) {
                    unsigned char* sp = smem + OFF_SS + (x * 32 + 8 * nt + 2 * t) * 80 + 8 * g;
                    *reinterpret_cast<float2*>(sp) = make_float2(S[nt][0], S[nt][2]);
                    *reinterpret_cast<float2*>(sp + 80) = make_float2(S[nt][1], S[nt][3]);
                }
                bar_sync(2, 256);
                CK1(c1)
                float s0 = 0.f, s1 = 0.f;
#pragma unroll
                for (int w = 0; w < 8; w++) {
                    const float2 v = *reinterpret_cast<const float2*>(smem + OFF_SS + (w * 32 + sh) * 80 + 8 * skp);
                    s0 += v.x; s1 += v.y;
                }
                s0 = bf16_round(bf16_round(s0) * SCALE);
                s1 = bf16_round(bf16_round(s1) * SCALE);
                float mx = fmaxf(s0, s1);
                mx = fmaxf(mx, __shfl_xor_sync(0xffffffffu, mx, 1));
                mx = fmaxf(mx, __shfl_xor_sync(0xffffffffu, mx, 2));
                mx = fmaxf(mx, __shfl_xor_sync(0xffffffffu, mx, 4));
                mx = fmaxf(mx, m);
                const float al = ex2((m - mx) * LOG2E);
                m = mx;
                const float p0 = ex2((s0 - m) * LOG2E), p1 = ex2((s1 - m) * LOG2E);
                l = l * al + p0 + p1;
                {
                    const uint32_t pp = pack_bf16(p0, p1);
                    uint16_t* dst = reinterpret_cast<uint16_t*>(smem + OFF_SP) + sh * 16 + kperm(skp);
                    dst[0] = (uint16_t)pp; dst[2] = (uint16_t)(pp >> 16);
                }
                if (skp == 0) reinterpret_cast<float*>(smem + OFF_ALPHA)[sh] = al;
                bar_sync(2, 256);
                CK1(c2)
                uint2 pb[4];
#pragma unroll
                for (int nt = 0; nt < 4; nt++) {
                    pb[nt] = *reinterpret_cast<const uint2*>(smem + OFF_SP + (8 * nt + g) * 32 + 8 * t);
                    const float2 a2 = *reinterpret_cast<const float2*>(smem + OFF_ALPHA + (8 * nt + 2 * t) * 4);
#pragma unroll
                    for (int mt = 0; mt < 4; mt++) {
                        acc[mt][nt][0] *= a2.x; acc[mt][nt][1] *= a2.y; acc[mt][nt][2] *= a2.x; acc[mt][nt][3] *= a2.y;
                    }
                }
                uint32_t dep = 0;
#pragma unroll
                for (int mt = 0; mt < 4; mt++) {
                    uint32_t a[4];
                    ldsm4t(a, base + (voff ^ (mt << 5)));
                    dep |= a[0];
#pragma unroll
                    for (int nt = 0; nt < 4; nt++) mma(acc[mt][nt], a[0], a[1], a[2], a[3], pb[nt].x, pb[nt].y);
                }
                xrel(n, dep);
                CK1(c3)
            }
#pragma unroll
            for (int nt = 0; nt < 4; nt++)
#pragma unroll
                for (int e = 0; e < 2; e++) {
                    float* dst = &H.S->pA[8 * nt + 2 * t + e][ab][asplit][64 * x + 4 * g];
                    *reinterpret_cast<float4*>(dst)      = make_float4(acc[0][nt][e], acc[0][nt][2 + e], acc[1][nt][e], acc[1][nt][2 + e]);
                    *reinterpret_cast<float4*>(dst + 32) = make_float4(acc[2][nt][e], acc[2][nt][2 + e], acc[3][nt][e], acc[3][nt][2 + e]);
                }
            l += __shfl_xor_sync(0xffffffffu, l, 1);
            l += __shfl_xor_sync(0xffffffffu, l, 2);
            l += __shfl_xor_sync(0xffffffffu, l, 4);
            if (skp == 0) H.S->mlA[sh][ab][asplit] = make_float2(m, l);
            bar_sync(2, 256);
            if (tid == 0) { add_rel(H.S->cntA); TL(9); }
        } else if (j >= 2) {
            uint32_t wv[4][4][4];
#pragma unroll
            for (int k = 0; k < 4; k++) {
                xwait(6 + k);
                uint32_t dep = 0;
                if (k == (x >> 1)) dep = load_wT<4>(wv, xr + ((6 + k) & 3) * CH_BYTES + (x & 1) * 8192, lane);
                xrel(6 + k, dep);
            }
            {
                const int b = tid >> 6, xx = (tid >> 3) & 7, gg = tid & 7;
                xwait(10 + b);
                if (tid == 0) TL(8);
                const float2* mlp = reinterpret_cast<const float2*>(smem + OFF_MLA) + b * A_SPLITS;
                float mm = -INFINITY, ll = 0.f;
#pragma unroll
                for (int s = 0; s < A_SPLITS; s++) mm = fmaxf(mm, mlp[s].x);
#pragma unroll
                for (int s = 0; s < A_SPLITS; s++) ll += mlp[s].y * ex2((mlp[s].x - mm) * LOG2E);
                const float inv = 1.f / ll;
                float cl[8];
#pragma unroll
                for (int e = 0; e < 8; e++) cl[e] = 0.f;
                const float* src = reinterpret_cast<const float*>(smem + OFF_XR + ((10 + b) & 3) * CH_BYTES) + 64 * xx + 4 * gg;
#pragma unroll
                for (int s = 0; s < A_SPLITS; s++) {
                    const float wt = ex2((mlp[s].x - mm) * LOG2E) * inv;
                    const float4 a = *reinterpret_cast<const float4*>(src + s * 512), c = *reinterpret_cast<const float4*>(src + s * 512 + 32);
                    cl[0] += wt * a.x; cl[1] += wt * a.y; cl[2] += wt * a.z; cl[3] += wt * a.w;
                    cl[4] += wt * c.x; cl[5] += wt * c.y; cl[6] += wt * c.z; cl[7] += wt * c.w;
                }
                uint16_t* hi = reinterpret_cast<uint16_t*>(smem + OFF_SS + b * 1056);
                uint16_t* lo = reinterpret_cast<uint16_t*>(smem + OFF_SS + (b + 4) * 1056);
#pragma unroll
                for (int e = 0; e < 8; e++) {
                    const int c = kperm(64 * xx + 8 * e + gg);
                    const float vh = bf16_round(cl[e]);
                    hi[c] = (uint16_t)(__float_as_uint(vh) >> 16);
                    lo[c] = (uint16_t)pack_bf16(cl[e] - vh, 0.f);
                }
                bar_sync(2, 256);
#pragma unroll
                for (int k = 0; k < 4; k++) xrel(10 + k, __float_as_uint(cl[0]) | __float_as_uint(cl[4]));
            }
            {
                float acc[4][4];
#pragma unroll
                for (int u = 0; u < 4; u++) acc[u][0] = acc[u][1] = acc[u][2] = acc[u][3] = 0.f;
#pragma unroll
                for (int s = 0; s < 4; s++) {
                    const uint2 b = *reinterpret_cast<const uint2*>(smem + OFF_SS + g * 1056 + (64 * x + 16 * s + 4 * t) * 2);
#pragma unroll
                    for (int mt = 0; mt < 4; mt++) mma(acc[mt], wv[s][mt][0], wv[s][mt][1], wv[s][mt][2], wv[s][mt][3], b.x, b.y);
                }
#pragma unroll
                for (int mt = 0; mt < 4; mt++)
#pragma unroll
                    for (int e = 0; e < 4; e++) acc[mt][e] += __shfl_xor_sync(0xffffffffu, acc[mt][e], 2);
                if (t < 2) {
#pragma unroll
                    for (int mt = 0; mt < 4; mt++) {
                        float* r0 = red + (x * 4 + 2 * t) * 64 + 16 * mt + g;
                        r0[0] = acc[mt][0]; r0[8] = acc[mt][2]; r0[64] = acc[mt][1]; r0[72] = acc[mt][3];
                    }
                }
            }
            bar_sync(2, 256);
            {
                float s = 0.f;
#pragma unroll
                for (int i = 0; i < 8; i++) s += red[i * 256 + tid];
                st_rlx(&H.S->vec[0][h][tid >> 6][kperm(64 * (j - 2) + (tid & 63))], (pack_bf16(0.f, s) & 0xffff0000u) | tag);
            }
            if (tid == 0) TL(9);
        }
        {
            __syncwarp();
            if (lane == 0) mbar_arrive(bar_xdone);
#pragma unroll 1
            for (uint32_t pass = H.zero; pass < 2; pass++) {
                if (pass == br) {
                    mbar_wait(br ? bar_cmb + 8 : bar_trig + 16, 0);
#pragma unroll 1
                    for (int u = 2 * x; u < 2 * x + 2; u++)
                        if (u < 15 || hl < HURG) gather128(&H.S->vec[br][hp + 8 * (u >> 2)][u & 3][0], tag, smem + OFF_SS + u * 288, lane, QD1);
                    __syncwarp();
                    if (lane == 0) { mbar_arrive(bar_vec); if (hl < HURG) mbar_arrive(bar_vec + 8); }
                    TL3(13, 0);
                    if (tid == 0) { H.S->epoch[bid] = ep; TL(10); }
                }
                if (pass ? hl >= HURG : (j < 3 || h < HURG)) {
                    const int pr = pass ? 96 + hl : 32 * j + h;
                    const uint32_t* rp = &H.S->pB[64 * pr + 8 * x][lane * 4];
                    const uint32_t* sp = &H.S->mlB[64 * pr + 8 * x + (lane & 7)][0];
                    uint4 v[8], sv;
                    mbar_wait(bar_cmb + pass * 16, 0);
                    TL3(5, 0);
                    if (lane == 0) {
                        mbar_expect_tx(bar_gat + x * 8, 4096 + 256);
                        bulk_load_nh(xr + x * 4096, rp, 4096, bar_gat + x * 8);
                        bulk_load_nh(sb + OFF_ST + x * 256, sp, 256, bar_gat + x * 8);
                    }
                    __syncwarp();
                    mbar_wait(bar_gat + x * 8, pass);
                    TL3(15, 0);
                    sv = lds128(sb + OFF_ST + x * 256 + (lane & 7) * 32);
#pragma unroll
                    for (int i = 0; i < 8; i++) v[i] = lds128(xr + x * 4096 + i * 512 + lane * 16);
                    float mx, ll, wt[8];
#pragma unroll 1
                    for (uint32_t it = 0;; it++) {
                        uint32_t bad[9];
#pragma unroll
                        for (int i = 0; i < 8; i++) bad[i] = untagged(v[i], par);
                        bad[8] = untagged(sv, par);
                        const uint32_t anyb = or3(or3(bad[0], bad[1], bad[2]), or3(bad[3], bad[4], bad[5]), or3(bad[6], bad[7], bad[8]));
                        const float m0 = __uint_as_float(sv.y);
                        mx = warp_max(m0);
                        const float w0 = ex2((m0 - mx) * LOG2E);
                        ll = w0 * __uint_as_float(sv.x);
                        const float l4 = __shfl_xor_sync(0xffffffffu, ll, 4);
#pragma unroll
                        for (int i = 0; i < 8; i++) wt[i] = __shfl_sync(0xffffffffu, w0, i);
                        ll += l4;
                        ll += __shfl_xor_sync(0xffffffffu, ll, 2);
                        if (!__any_sync(0xffffffffu, anyb & 1) || it >= SPIN_LIMIT) break;
                        uint32_t mask = 0;
#pragma unroll
                        for (int i = 0; i < 9; i++) mask |= (bad[i] & 1) << i;
                        const uint32_t pend = __reduce_or_sync(0xffffffffu, mask);
                        ld_rlx2x64_if(sv, sp, pend & 256);
#pragma unroll
                        for (int i = 0; i < 8; i++) ld_rlx2x64_if(v[i], rp + i * 128, pend & (1 << i));
                    }
                    ll += __shfl_xor_sync(0xffffffffu, ll, 1);
                    float4 acc = make_float4(0.f, 0.f, 0.f, 0.f), acd = acc;
#pragma unroll
                    for (int i = 0; i < 8; i += 2) {
                        acc.x += wt[i] * __uint_as_float(v[i].x); acc.y += wt[i] * __uint_as_float(v[i].y);
                        acc.z += wt[i] * __uint_as_float(v[i].z); acc.w += wt[i] * __uint_as_float(v[i].w);
                        acd.x += wt[i + 1] * __uint_as_float(v[i + 1].x); acd.y += wt[i + 1] * __uint_as_float(v[i + 1].y);
                        acd.z += wt[i + 1] * __uint_as_float(v[i + 1].z); acd.w += wt[i + 1] * __uint_as_float(v[i + 1].w);
                    }
                    acc.x += acd.x; acc.y += acd.y; acc.z += acd.z; acc.w += acd.w;
                    TL3(6, 0);
                    if (lane == 0) reinterpret_cast<float2*>(red + 1024)[x] = make_float2(mx, ll);
                    reinterpret_cast<float4*>(red)[tid] = acc;
                    const int d = kperm(16 * ((tid >> 2) & 3) + 8 * (tid & 1) + 64 * ((tid >> 1) & 1) + ((tid >> 4) & 7));
                    uint32_t od = sb + OFF_SS + 15 * 288 + 2 * d, ra = sb + OFF_SS + 8448;
                    asm volatile("" : "+r"(od), "+r"(ra));
                    bar_sync(2, 256);
                    if (x < 4) {
                        uint4 st[4];
                        float r[8];
#pragma unroll
                        for (int i = 0; i < 4; i++) st[i] = lds128(ra + 4096 + 16 * i);
#pragma unroll
                        for (int i = 0; i < 8; i++) r[i] = lds32(ra + 512 * i + 4 * tid);
                        float m2[4];
#pragma unroll
                        for (int i = 0; i < 4; i++) m2[i] = fmaxf(__uint_as_float(st[i].x), __uint_as_float(st[i].z));
                        const float mm = fmaxf(fmaxf(m2[0], m2[1]), fmaxf(m2[2], m2[3]));
                        float s0 = 0.f, s1 = 0.f, l0 = 0.f, l1 = 0.f;
#pragma unroll
                        for (int i = 0; i < 4; i++) {
                            const float f0 = ex2((__uint_as_float(st[i].x) - mm) * LOG2E), f1 = ex2((__uint_as_float(st[i].z) - mm) * LOG2E);
                            s0 += f0 * r[2 * i]; s1 += f1 * r[2 * i + 1];
                            l0 += f0 * __uint_as_float(st[i].y); l1 += f1 * __uint_as_float(st[i].w);
                        }
                        float inv;
                        asm("rcp.approx.ftz.f32 %0, %1;" : "=f"(inv) : "f"(l0 + l1));
                        const uint32_t ob = pack_bf16((s0 + s1) * inv, 0.f);
                        if (pass) asm volatile("st.shared.u16 [%0], %1;" :: "r"(od), "h"((uint16_t)ob) : "memory");
                        else st_rlx(&H.S->vec[1][h][j][d], (ob << 16) | tag);
                    }
                    __syncwarp();
                    if (pass && lane == 0) mbar_arrive(bar_vec + 8);
                    TL3(7, 0);
                    if (!pass) bar_sync(2, 256);
                }
            }
        }
    }
}

typedef CUresult (*EncodeFn)(CUtensorMap*, CUtensorMapDataType, cuuint32_t, void*, const cuuint64_t*, const cuuint64_t*,
                             const cuuint32_t*, const cuuint32_t*, CUtensorMapInterleave, CUtensorMapSwizzle,
                             CUtensorMapL2promotion, CUtensorMapFloatOOBfill);

void encode2d(EncodeFn fn, CUtensorMap* tm, void* ptr, uint64_t cols, uint64_t rows, uint32_t box_rows) {
    const cuuint64_t dims[2] = {cols, rows};
    const cuuint64_t strides[1] = {cols * 2};
    const cuuint32_t box[2] = {64, box_rows};
    const cuuint32_t es[2] = {1, 1};
    fn(tm, CU_TENSOR_MAP_DATA_TYPE_BFLOAT16, 2, ptr, dims, strides, box, es, CU_TENSOR_MAP_INTERLEAVE_NONE,
       CU_TENSOR_MAP_SWIZZLE_128B, CU_TENSOR_MAP_L2_PROMOTION_NONE, CU_TENSOR_MAP_FLOAT_OOB_FILL_NONE);
}

}

extern "C" void kernel_launch(void* const* d_in, const int* in_sizes, int n_in, void* d_out, int out_size) {
    (void)in_sizes; (void)n_in; (void)out_size;
    static EncodeFn encode = nullptr;
    static Scratch* scratch = nullptr;
    if (!encode) {
        cudaFuncSetAttribute(fused_decode_kernel, cudaFuncAttributeMaxDynamicSharedMemorySize, SMEM_BYTES + SMEM_EXTRA);
        void* fn = nullptr;
        cudaDriverEntryPointQueryResult qr;
        cudaGetDriverEntryPoint("cuTensorMapEncodeTiled", &fn, cudaEnableDefault, &qr);
        encode = (EncodeFn)fn;
        void* sp = nullptr;
        cudaGetSymbolAddress(&sp, g_scratch);
        scratch = (Scratch*)sp;
    }
    Params p;
    encode2d(encode, &p.tm_wq[0], d_in[9], 4096, 512, 128);
    encode2d(encode, &p.tm_wq[1], d_in[2], 4096, 512, 128);
    encode2d(encode, &p.tm_wuk,   d_in[3], 4096, 512, 128);
    encode2d(encode, &p.tm_wuv,   d_in[4], 4096, 512, 128);
    encode2d(encode, &p.tm_wo[1], d_in[10], 512, 4096, 128);
    encode2d(encode, &p.tm_wo[0], d_in[5], 512, 4096, 128);
    {
        const cuuint64_t dims[3] = {64, 16384, 8};
        const cuuint64_t strides[2] = {1024, 128};
        const cuuint32_t box[3] = {64, 16, 8};
        const cuuint32_t es[3] = {1, 1, 1};
        encode(&p.tm_ckv, CU_TENSOR_MAP_DATA_TYPE_BFLOAT16, 3, d_in[1], dims, strides, box, es, CU_TENSOR_MAP_INTERLEAVE_NONE,
               CU_TENSOR_MAP_SWIZZLE_128B, CU_TENSOR_MAP_L2_PROMOTION_NONE, CU_TENSOR_MAP_FLOAT_OOB_FILL_NONE);
    }
    p.wo[0] = (const __nv_bfloat16*)d_in[5];
    p.wo[1] = (const __nv_bfloat16*)d_in[10];
    p.out = (__nv_bfloat16*)d_out;
    Hot hp;
    hp.kp = (const char*)d_in[7];
    hp.vp = (const char*)d_in[8];
    hp.S = scratch;
    hp.x[0] = (const __nv_bfloat16*)d_in[6];
    hp.x[1] = (const __nv_bfloat16*)d_in[0];
    hp.zero = 0;
    cudaLaunchConfig_t cfg = {};
    cfg.gridDim = dim3(NCTA);
    cfg.blockDim = dim3(NTHREADS);
    cfg.dynamicSmemBytes = SMEM_BYTES + SMEM_EXTRA;
    cfg.stream = cudaStreamPerThread;
    cudaLaunchAttribute at[1];
    at[0].id = cudaLaunchAttributeCooperative;
    at[0].val.cooperative = 1;
    cfg.attrs = at;
    cfg.numAttrs = 1;
    cudaLaunchKernelEx(&cfg, fused_decode_kernel, hp, p);
}
```

```cpp
#include <cuda_runtime.h>
#include <cuda.h>
#include <cuda_bf16.h>
#include <stdint.h>

namespace {

constexpr int NCTA      = 128;
constexpr int NTHREADS  = 512;
constexpr int CH_BYTES  = 16384;
constexpr int NPIECE    = 128 * 64;
constexpr int RING      = 8;
#define PFV 10240
#define WIN 3
#define DL0 3100
#define DLS 1000
#define NB2 4500
#define NBS 1300
#define DLR 18
#define DLQ 20
#define HS 31
#define XS 224
#define TG 5700
#define LAG 192
#define LAG2 96
#define LAG1 192
#define HURG 24
#define FSLEEP 600
#define QSLEEP 400
#define QD0 600
#define QD1 100
#define TRIG0 (20 * 128)
#define TRIG1 (32 * 128)
#define TRIG2 (50 * 128)
constexpr int SMEM_EXTRA = 0;
constexpr int A_SPLITS  = 8;
constexpr int A_TILES   = 4096 / A_SPLITS / 16;

constexpr int OFF_RING  = 0;
constexpr int OFF_XR    = OFF_RING + RING * CH_BYTES;
constexpr int OFF_SS    = OFF_XR + 4 * CH_BYTES;
constexpr int OFF_SP    = OFF_SS + 8 * 32 * 80;
constexpr int OFF_ALPHA = OFF_SP + 1024;
constexpr int OFF_OA    = OFF_ALPHA + 128;
constexpr int OFF_ST    = OFF_OA + 4 * 288;
constexpr int OFF_MLA   = OFF_ST + 64 * 32;
constexpr int OFF_QT    = OFF_MLA + 4 * A_SPLITS * 8;
constexpr int MG_BYTES  = 2048 + 128 + 32;
constexpr int OFF_MG    = OFF_QT + 4 * 256;
constexpr int OFF_META  = OFF_MG + 2 * MG_BYTES;
constexpr int OFF_EP    = OFF_META + 16;
constexpr int OFF_X     = OFF_SS + 4096;
constexpr int OFF_BAR   = OFF_EP + 16;
constexpr int NBAR      = 2 * RING + 8 + 2 + 3 + 4 + 3 + 1 + 8 + 8 + 2 + 2 + 2 + 1;
constexpr int I_INI     = 2 * RING + 8 + 2 + 3 + 4 + 3;
constexpr int SMEM_BYTES = OFF_BAR + NBAR * 8;

constexpr float LOG2E = 1.4426950408889634f;
constexpr float SCALE = 0.08838834764831845f;
constexpr uint32_t SPIN_LIMIT = 1u << 20;

struct Scratch {
    uint32_t ticket[2][64];
    uint32_t epoch[NCTA];
    uint32_t cntQ[64], cntA[64];
    float2   mlA[32][4][A_SPLITS];
    uint32_t vec[2][32][4][128];
    uint32_t q[2][4][4096];
    uint16_t qabs[4][8][2][4][2][32][8];
    float    pA[32][4][A_SPLITS][512];
    uint32_t pB[NPIECE][128];
    uint32_t mlB[NPIECE][8];
};
__device__ __align__(128) Scratch g_scratch;
#define TL(i) do {} while (0)
#define TL3(i, dep) do {} while (0)
#define TLG(i) do {} while (0)
#define TL2(i) do {} while (0)

struct Hot {
    const char *kp, *vp;
    Scratch* S;
    const __nv_bfloat16* x[2];
    uint32_t zero;
    uint32_t never;
};
struct Params {
    CUtensorMap tm_wq[2];
    CUtensorMap tm_wuk, tm_wuv;
    CUtensorMap tm_wo[2];
    CUtensorMap tm_ckv;
    const __nv_bfloat16* wo[2];
    __nv_bfloat16* out;
};

__device__ __forceinline__ void mbar_init(uint32_t bar, uint32_t cnt) {
    asm volatile("mbarrier.init.shared::cta.b64 [%0], %1;" :: "r"(bar), "r"(cnt) : "memory");
}
__device__ __forceinline__ void mbar_expect_tx(uint32_t bar, uint32_t bytes) {
    asm volatile("mbarrier.arrive.expect_tx.shared::cta.b64 _, [%0], %1;" :: "r"(bar), "r"(bytes) : "memory");
}
__device__ __forceinline__ void mbar_arrive(uint32_t bar) {
    asm volatile("mbarrier.arrive.shared::cta.b64 _, [%0];" :: "r"(bar) : "memory");
}
template <uint32_t LIMIT = SPIN_LIMIT>
__device__ __forceinline__ bool mbar_wait(uint32_t bar, uint32_t parity) {
    uint32_t done, it = 0;
    do {
        asm volatile("{\n.reg .pred p;\nmbarrier.try_wait.parity.shared::cta.b64 p, [%1], %2;\nselp.u32 %0, 1, 0, p;\n}"
                     : "=r"(done) : "r"(bar), "r"(parity) : "memory");
        if (++it > LIMIT) break;
    } while (!done);
    return done;
}
__device__ __forceinline__ void bulk_load(uint32_t dst, const void* src, uint32_t bytes, uint32_t bar, uint64_t pol) {
    asm volatile("cp.async.bulk.shared::cluster.global.mbarrier::complete_tx::bytes.L2::cache_hint [%0], [%1], %2, [%3], %4;"
                 :: "r"(dst), "l"(src), "r"(bytes), "r"(bar), "l"(pol) : "memory");
}
__device__ __forceinline__ uint64_t policy_evict_first() {
    uint64_t pol;
    asm volatile("createpolicy.fractional.L2::evict_first.b64 %0, 1.0;" : "=l"(pol));
    return pol;
}
__device__ __forceinline__ void bar_sync(int id, int n)   { asm volatile("bar.sync %0, %1;" :: "r"(id), "r"(n) : "memory"); }
__device__ __forceinline__ void bar_arrive(int id, int n) { asm volatile("bar.arrive %0, %1;" :: "r"(id), "r"(n) : "memory"); }
__device__ __forceinline__ void ldsm4(uint32_t (&r)[4], uint32_t addr) {
    asm volatile("ldmatrix.sync.aligned.m8n8.x4.shared.b16 {%0,%1,%2,%3}, [%4];"
                 : "=r"(r[0]), "=r"(r[1]), "=r"(r[2]), "=r"(r[3]) : "r"(addr) : "memory");
}
__device__ __forceinline__ void ldsm4t(uint32_t (&r)[4], uint32_t addr) {
    asm volatile("ldmatrix.sync.aligned.m8n8.x4.trans.shared.b16 {%0,%1,%2,%3}, [%4];"
                 : "=r"(r[0]), "=r"(r[1]), "=r"(r[2]), "=r"(r[3]) : "r"(addr) : "memory");
}
__device__ __forceinline__ void mma(float (&c)[4], uint32_t a0, uint32_t a1, uint32_t a2, uint32_t a3, uint32_t b0, uint32_t b1) {
    asm volatile("mma.sync.aligned.m16n8k16.row.col.f32.bf16.bf16.f32 {%0,%1,%2,%3}, {%4,%5,%6,%7}, {%8,%9}, {%0,%1,%2,%3};"
                 : "+f"(c[0]), "+f"(c[1]), "+f"(c[2]), "+f"(c[3])
                 : "r"(a0), "r"(a1), "r"(a2), "r"(a3), "r"(b0), "r"(b1));
}
__device__ __forceinline__ uint32_t prmt(uint32_t a, uint32_t b, uint32_t s) {
    uint32_t r; asm("prmt.b32 %0, %1, %2, %3;" : "=r"(r) : "r"(a), "r"(b), "r"(s)); return r;
}
__device__ __forceinline__ uint32_t pack_bf16(float lo, float hi) {
    uint32_t r; asm("cvt.rn.bf16x2.f32 %0, %1, %2;" : "=r"(r) : "f"(hi), "f"(lo)); return r;
}
__device__ __forceinline__ float bf16_round(float v) { return __uint_as_float(pack_bf16(0.f, v) & 0xffff0000u); }
__device__ __forceinline__ float ex2(float x) { float r; asm("ex2.approx.ftz.f32 %0, %1;" : "=f"(r) : "f"(x)); return r; }
__device__ __forceinline__ uint4 ld_rlx4(const void* p) {
    uint4 v;
    asm volatile("ld.relaxed.gpu.global.v4.u32 {%0,%1,%2,%3}, [%4];" : "=r"(v.x), "=r"(v.y), "=r"(v.z), "=r"(v.w) : "l"(p) : "memory");
    return v;
}
__device__ __forceinline__ uint32_t ld_acq(const void* p) {
    uint32_t v; asm volatile("ld.acquire.gpu.global.u32 %0, [%1];" : "=r"(v) : "l"(p) : "memory"); return v;
}
__device__ __forceinline__ void st_rlx(void* p, uint32_t v) { asm volatile("st.relaxed.gpu.global.u32 [%0], %1;" :: "l"(p), "r"(v) : "memory"); }
__device__ __forceinline__ void st_rlx4(void* p, uint32_t a, uint32_t b, uint32_t c, uint32_t d) {
    asm volatile("st.relaxed.gpu.global.v4.u32 [%0], {%1,%2,%3,%4};" :: "l"(p), "r"(a), "r"(b), "r"(c), "r"(d) : "memory");
}
__device__ __forceinline__ float warp_max(float v) {
    int k = __float_as_int(v);
    k ^= (k >> 31) & 0x7fffffff;
    k = __reduce_max_sync(0xffffffffu, k);
    k ^= (k >> 31) & 0x7fffffff;
    return __int_as_float(k);
}
__device__ __forceinline__ uint32_t tagf(float v, uint32_t par) { return (__float_as_uint(v) & ~1u) | par; }
__device__ __forceinline__ void wait_count(const uint32_t* c, uint32_t val, uint32_t sleep) {
#pragma unroll 1
    for (uint32_t it = 0; it < SPIN_LIMIT && ld_acq(c) != val; it++) __nanosleep(sleep);
}
__device__ __forceinline__ uint32_t take_ticket(uint32_t* c) {
    uint32_t v; asm volatile("atom.relaxed.gpu.global.add.u32 %0, [%1], 1;" : "=r"(v) : "l"(c) : "memory"); return v;
}
__device__ __forceinline__ void add_rel(uint32_t* c) { asm volatile("red.release.gpu.global.add.u32 [%0], 1;" :: "l"(c) : "memory"); }
__device__ __forceinline__ uint32_t tag16(uint32_t ep) { return (ep & 0x7fffu) | 0x8000u; }
__device__ __forceinline__ void gather128(const uint32_t* src, uint32_t tag, unsigned char* dst, int lane, uint32_t sleep) {
    uint4 v;
#pragma unroll 1
    for (uint32_t it = 0; it < SPIN_LIMIT; it++) {
        v = ld_rlx4(src + lane * 4);
        const bool ok = ((((v.x ^ tag) | (v.y ^ tag)) | ((v.z ^ tag) | (v.w ^ tag))) & 0xffffu) == 0;
        if (__all_sync(0xffffffffu, ok)) break;
        __nanosleep(sleep);
    }
    *reinterpret_cast<uint2*>(dst + lane * 8) = make_uint2(prmt(v.x, v.y, 0x7632), prmt(v.z, v.w, 0x7632));
}

__device__ __forceinline__ void bulk_load_nh(uint32_t dst, const void* src, uint32_t bytes, uint32_t bar) {
    asm volatile("cp.async.bulk.shared::cluster.global.mbarrier::complete_tx::bytes [%0], [%1], %2, [%3];"
                 :: "r"(dst), "l"(src), "r"(bytes), "r"(bar) : "memory");
}
__device__ __forceinline__ void tma2d_hint(uint32_t dst, const CUtensorMap* tm, int c0, int c1, uint32_t bar, uint64_t pol) {
    asm volatile("cp.async.bulk.tensor.2d.shared::cluster.global.mbarrier::complete_tx::bytes.L2::cache_hint [%0], [%1, {%3, %4}], [%2], %5;"
                 :: "r"(dst), "l"(tm), "r"(bar), "r"(c0), "r"(c1), "l"(pol) : "memory");
}
__device__ __forceinline__ void tma3d_hint(uint32_t dst, const CUtensorMap* tm, int c0, int c1, int c2, uint32_t bar, uint64_t pol) {
    asm volatile("cp.async.bulk.tensor.3d.shared::cluster.global.mbarrier::complete_tx::bytes.L2::cache_hint [%0], [%1, {%3, %4, %5}], [%2], %6;"
                 :: "r"(dst), "l"(tm), "r"(bar), "r"(c0), "r"(c1), "r"(c2), "l"(pol) : "memory");
}
__device__ __forceinline__ void prefetch32(const void* p) { asm volatile("cp.async.bulk.prefetch.L2.global [%0], 32;" :: "l"(p) : "memory"); }
__device__ __forceinline__ void prefetch_tm(const CUtensorMap* tm) { asm volatile("prefetch.tensormap [%0];" :: "l"(tm) : "memory"); }
__device__ __forceinline__ int kperm(int d) { return (d & ~15) | ((d & 6) << 1) | ((d >> 2) & 2) | (d & 1); }

template <int NK>
__device__ __forceinline__ uint32_t load_wT(uint32_t (&w)[NK][4][4], uint32_t base, int lane) {
    const int r8 = lane & 7;
    const uint32_t a0 = base + (r8 + 8 * (lane >> 4)) * 128 + ((((lane >> 3) & 1) ^ r8) << 4);
    uint32_t dep = 0;
#pragma unroll
    for (int s = 0; s < NK; s++)
#pragma unroll
        for (int mt = 0; mt < 4; mt++) { ldsm4t(w[s][mt], (a0 ^ (mt << 5)) + s * 2048); dep |= w[s][mt][0]; }
    return dep;
}

__device__ __forceinline__ bool mbar_test(uint32_t bar, uint32_t parity) {
    uint32_t done;
    asm volatile("{\n.reg .pred p;\nmbarrier.test_wait.parity.shared::cta.b64 p, [%1], %2;\nselp.u32 %0, 1, 0, p;\n}"
                 : "=r"(done) : "r"(bar), "r"(parity) : "memory");
    return done;
}
__device__ __forceinline__ void st_rlx2x64(void* p, uint32_t a, uint32_t b, uint32_t c, uint32_t d) {
    asm volatile("{\n.reg .b64 u, v;\nmov.b64 u, {%1,%2};\nmov.b64 v, {%3,%4};\nst.relaxed.gpu.global.v2.b64 [%0], {u, v};\n}"
                 :: "l"(p), "r"(a), "r"(b), "r"(c), "r"(d) : "memory");
}
__device__ __forceinline__ void ld_rlx2x64_if(uint4& v, const void* p, uint32_t pred) {
    asm volatile("{\n.reg .pred p;\n.reg .b64 u, v;\nsetp.ne.u32 p, %5, 0;\nmov.b64 u, {%0,%1};\nmov.b64 v, {%2,%3};\n"
                 "@p ld.relaxed.gpu.global.v2.b64 {u, v}, [%4];\nmov.b64 {%0,%1}, u;\nmov.b64 {%2,%3}, v;\n}"
                 : "+r"(v.x), "+r"(v.y), "+r"(v.z), "+r"(v.w) : "l"(p), "r"(pred) : "memory");
}
__device__ __forceinline__ uint4 lds128(uint32_t a) {
    uint4 v; asm volatile("ld.shared.v4.u32 {%0,%1,%2,%3}, [%4];" : "=r"(v.x), "=r"(v.y), "=r"(v.z), "=r"(v.w) : "r"(a) : "memory"); return v;
}
__device__ __forceinline__ float lds32(uint32_t a) { float v; asm volatile("ld.shared.f32 %0, [%1];" : "=f"(v) : "r"(a) : "memory"); return v; }
__device__ __forceinline__ uint32_t untagged(const uint4& v, uint32_t par) {
    uint32_t bad;
    asm("lop3.b32 %0, %1, %2, %3, 0x7e;" : "=r"(bad) : "r"(v.x), "r"(v.z), "r"(par));
    return bad;
}
__device__ __forceinline__ uint32_t or3(uint32_t a, uint32_t b, uint32_t c) {
    uint32_t r; asm("lop3.b32 %0, %1, %2, %3, 0xfe;" : "=r"(r) : "r"(a), "r"(b), "r"(c)); return r;
}
__device__ __forceinline__ void red_bf2(void* p, uint32_t v, uint32_t pred) {
    asm volatile("{\n.reg .pred p;\nsetp.ne.u32 p, %2, 0;\n@p red.relaxed.gpu.global.add.noftz.bf16x2 [%0], %1;\n}" :: "l"(p), "r"(v), "r"(pred) : "memory");
}

__global__ void __launch_bounds__(NTHREADS, 1) fused_decode_kernel(const __grid_constant__ Hot H, const __grid_constant__ Params P) {
    asm volatile("{\n.reg .pred p;\nsetp.eq.u32 p, %2, 0;\n@p cp.async.bulk.prefetch.L2.global [%0], %1;\n}"
                 :: "l"(H.vp + (size_t)blockIdx.x * CH_BYTES), "n"(PFV), "r"(threadIdx.x) : "memory");
    if (H.never) return;
    const uint64_t pol = policy_evict_first();
    extern __shared__ __align__(1024) unsigned char smem[];
    const uint32_t sb = (uint32_t)__cvta_generic_to_shared(smem);
    const int bid = blockIdx.x, h = bid >> 2, j = bid & 3;
    const int lane = threadIdx.x & 31;
    const int g = lane >> 2, t = lane & 3;
    const uint32_t bar_full = sb + OFF_BAR, bar_empty = bar_full + RING * 8;
    const uint32_t bar_xfull = bar_empty + RING * 8, bar_xempty = bar_xfull + 32, bar_vec = bar_xempty + 32, bar_trig = bar_vec + 16;
    const uint32_t bar_wo = bar_trig + 24, bar_cmb = bar_wo + 32, bar_ini = bar_cmb + 24, bar_gat = bar_ini + 8, bar_qreq = bar_gat + 64, bar_qfull = bar_qreq + 32;
    const uint32_t bar_mempty = bar_qfull + 32, bar_mfull = bar_mempty + 16;
    const uint32_t bar_sfull = bar_mfull + 16, bar_xdone = bar_sfull + 16;
    const int mat = bid & 1, cb = bid >> 1;
    const int ab = h & 3, asplit = h >> 2;
    const int br = j < 2, hp = h & 7, cbk = 2 * (h >> 3) + (j & 1);
    const int hl = br ? 24 + hp : 0;

    const char* kp = H.kp;
    const char* vp = H.vp;
    if (threadIdx.x == 0) {
        mbar_init(bar_full, 1);
        asm volatile("fence.mbarrier_init.release.cluster;" ::: "memory");
        mbar_expect_tx(bar_full, CH_BYTES);
        bulk_load(sb + OFF_RING, kp + bid * CH_BYTES, CH_BYTES, bar_full, pol);
        TL(0); TLG(0);
#pragma unroll
        for (int i = 0; i < 4; i++) mbar_init(bar_xfull + i * 8, 1);
        mbar_init(bar_full + 8, 1);
        mbar_init(bar_ini, 1);
        asm volatile("fence.mbarrier_init.release.cluster;" ::: "memory");
#pragma unroll
        for (int i = 0; i < 4; i++) {
            mbar_expect_tx(bar_xfull + i * 8, CH_BYTES);
            tma2d_hint(sb + OFF_XR + i * CH_BYTES, &P.tm_wq[mat], 64 * cb, 128 * i, bar_xfull + i * 8, pol);
            if (i == 0) {
                mbar_expect_tx(bar_full + 8, CH_BYTES);
                bulk_load(sb + OFF_RING + CH_BYTES, vp + bid * CH_BYTES, CH_BYTES, bar_full + 8, pol);
                mbar_expect_tx(bar_ini, 4096 + 16);
                bulk_load_nh(sb + OFF_EP, &H.S->epoch[4 * h], 16, bar_ini);
                bulk_load_nh(sb + OFF_X, H.x[mat], 4096, bar_ini);
            }
        }
        *reinterpret_cast<int*>(smem + OFF_META) = bid;
#pragma unroll
        for (int i = 2; i < NBAR; i++)
            if ((i < 2 * RING || i >= 2 * RING + 4) && i != I_INI)
                mbar_init(bar_full + i * 8, ((i >= RING && i < 2 * RING) || (i >= NBAR - 5 && i < NBAR - 1)) ? 4
                                          : (i >= 2 * RING + 4 && i < 2 * RING + 10) ? 8 : i == NBAR - 1 ? 9 : 1);
        asm volatile("fence.mbarrier_init.release.cluster;" ::: "memory");
        mbar_arrive(bar_qreq);
    }

    __syncwarp();
    const int warp = __shfl_sync(0xffffffffu, threadIdx.x >> 5, 0);
    auto epoch = [&]() -> uint32_t {
        mbar_wait(bar_ini, 0);
        return __shfl_sync(0xffffffffu, reinterpret_cast<const uint32_t*>(smem + OFF_EP)[j], 0) + 1;
    };

    if (warp >= 12) {
        asm volatile("setmaxnreg.dec.sync.aligned.u32 40;");
        bar_sync(1, 512);
        const uint32_t ep = epoch();
        if (warp == 12) {
            if (lane == 0) {
                uint32_t* tick = &H.S->ticket[ep & 1][threadIdx.x & H.zero];
                if (bid == 0) H.S->ticket[(ep & 1) ^ 1][0] = 0;
                int ntrig = 0, piece = bid, i = 2;
                uint32_t next = 0, tclaim = 0;
#pragma unroll 1
                for (;; i++) {
                    const int s = i % RING;
                    if (i <= 4) mbar_wait<2048>(bar_xfull + (i - 2) * 8, 0);
                    if (i >= WIN) {
                        mbar_wait(bar_full + ((i - WIN) % RING) * 8, ((i - WIN) / RING) & 1);
                        if (i - WIN < 192) TL2(i - WIN);
                    }
                    if (i >= RING && !mbar_wait(bar_empty + s * 8, ((i / RING) - 1) & 1)) break;
                    if (!(i & 1)) {
                        piece = i == 2 ? NCTA + bid : 2 * NCTA + (int)next;
                        reinterpret_cast<volatile int*>(smem + OFF_META)[s >> 1] = piece < NPIECE ? piece : -1;
                        mbar_arrive(bar_qreq + (s >> 1) * 8);
                        while (ntrig < 3 && piece >= (ntrig == 0 ? TRIG0 : ntrig == 1 ? TRIG1 : TRIG2)) mbar_arrive(bar_trig + 8 * ntrig++);
                        if (piece >= NPIECE) break;
                    }
                    mbar_expect_tx(bar_full + s * 8, CH_BYTES);
                    bulk_load(sb + OFF_RING + s * CH_BYTES, ((i & 1) ? vp : kp) + (size_t)piece * CH_BYTES, CH_BYTES, bar_full + s * 8, pol);
                    if ((piece & 127) == 0 && piece + 2 * NCTA < NPIECE) prefetch32(((i & 1) ? vp : kp) + (size_t)(piece + 2 * NCTA) * CH_BYTES);
                    if ((piece >> 7) == 60) prefetch32(P.wo[br] + (hp + 16 * (i & 1)) * 65536 + 64 * cbk);
                    if (i & 1) {
                        if (hl >= HS && piece >= NPIECE - XS) {
                            tclaim += (NPIECE - piece) * DLR;
                            next = NPIECE - 2 * NCTA;
                        } else { next = take_ticket(tick); tclaim = clock(); }
                    }
                }
                const uint32_t tg = tclaim - (piece - NPIECE) * DLQ;
                mbar_wait(bar_xdone, 0);
                if (i >= RING) mbar_wait(bar_empty + (i % RING) * 8 + 8, ((i / RING) - 1) & 1);
                const int tlook = TG - (31 - hl) * 64 * DLR;
                bool look = hl >= HS;
                auto since = [&]() -> int {
                    const int now = (int)((uint32_t)clock() - tg);
                    if (look && now >= tlook) { mbar_arrive(bar_cmb + 16); look = false; }
                    return now;
                };
#pragma unroll 1
                for (int k = 0; k < 4; k++) {
                    const uint32_t dst = sb + (k < 2 ? OFF_RING + (i % RING) * CH_BYTES : OFF_XR) + k * CH_BYTES;
                    const int wi = k - 2;
                    const uint32_t wb = wi >= 0 ? bar_wo + wi * 8 : bar_full + ((i + wi) % RING) * 8, wp = wi >= 0 ? 0 : ((i + wi) / RING) & 1;
                    while (wi >= 0 && hl < HS && since() < NB2 + wi * NBS) {}
                    while (!mbar_test(wb, wp) && since() < DL0 + k * DLS) {}
                    mbar_expect_tx(bar_wo + k * 8, CH_BYTES);
                    tma2d_hint(dst, &P.tm_wo[br], 64 * cbk, (hp + 8 * k) * 128, bar_wo + k * 8, pol);
                }
                while (look) since();
                TL(1);
            }
        } else if (warp == 15) {
            const uint32_t par = ep & 1;
            const uint32_t t0 = 64 * (32 * j + h + 1) + LAG, t1 = 64 * (96 + (hl < HURG ? hl : hl - 8) + 1) + LAG + LAG1, t2 = 64 * (96 + hl + 1) + LAG2;
            uint32_t fired = 0;
#pragma unroll 1
            for (int r = 0;; r++) {
                const unsigned char* mg = smem + OFF_MG + (r & 1) * MG_BYTES;
                if (!mbar_wait(bar_sfull + (r & 1) * 8, (r >> 1) & 1)) break;
                const uint32_t piece = *reinterpret_cast<const uint32_t*>(mg + 2048 + 144);
                if (piece < NPIECE) {
                    const float4 mw = *reinterpret_cast<const float4*>(mg + 2048 + 128);
                    const float mm = fmaxf(fmaxf(mw.x, mw.y), fmaxf(mw.z, mw.w));
                    const float e0 = ex2((mw.x - mm) * LOG2E), e1 = ex2((mw.y - mm) * LOG2E);
                    const float e2 = ex2((mw.z - mm) * LOG2E), e3 = ex2((mw.w - mm) * LOG2E);
                    float l = reinterpret_cast<const float*>(mg + 2048)[lane] * ((lane & 16) ? ((lane & 8) ? e3 : e2) : ((lane & 8) ? e1 : e0));
#pragma unroll
                    for (int o = 16; o > 0; o >>= 1) l += __shfl_xor_sync(0xffffffffu, l, o);
                    uint32_t* dst = &H.S->pB[piece][lane * 4];
                    if (piece >= NPIECE - 512) mbar_wait(bar_xdone, 0);
                    if (lane < 2) st_rlx2x64(&H.S->mlB[piece][lane * 4], tagf(l, par), __float_as_uint(mm), par, 0);
                    mbar_wait(bar_mfull + (r & 1) * 8, (r >> 1) & 1);
                    const float4 a = reinterpret_cast<const float4*>(mg)[lane],      b = reinterpret_cast<const float4*>(mg)[32 + lane];
                    const float4 c = reinterpret_cast<const float4*>(mg)[64 + lane], d = reinterpret_cast<const float4*>(mg)[96 + lane];
                    st_rlx2x64(dst, tagf((a.x * e0 + b.x * e1) + (c.x * e2 + d.x * e3), par), __float_as_uint((a.y * e0 + b.y * e1) + (c.y * e2 + d.y * e3)),
                                    tagf((a.z * e0 + b.z * e1) + (c.z * e2 + d.z * e3), par), __float_as_uint((a.w * e0 + b.w * e1) + (c.w * e2 + d.w * e3)));
                    TL3(3, 0);
                }
                __syncwarp();
                const uint32_t now = (piece >= t0 ? 1u : 0u) | (piece >= t1 ? 2u : 0u) | (piece >= t2 && hl < HS ? 4u : 0u);
                if (lane < 3 && ((now & ~fired) >> lane & 1)) mbar_arrive(bar_cmb + lane * 8);
                fired = now;
                if (piece >= NPIECE) break;
                if (lane == 0) mbar_arrive(bar_mempty + (r & 1) * 8);
            }
        } else if (warp == 14) {
            mbar_wait<2048>(bar_xfull + 24, 0);
            __nanosleep(QD0);
#pragma unroll 1
            for (int r = 0;; r++) {
                if (!mbar_wait(bar_qreq + (r & 3) * 8, (r >> 2) & 1)) break;
                const int piece = reinterpret_cast<volatile int*>(smem + OFF_META)[r & 3];
                if (piece >= 0) gather128(&H.S->q[0][piece >> 11][((piece >> 6) & 31) * 128], tag16(ep), smem + OFF_QT + (r & 3) * 256, lane, QD1);
                __syncwarp();
                if (lane == 0) mbar_arrive(bar_qfull + (r & 3) * 8);
                if (piece < 0) break;
            }
        } else if (warp == 13) {
            if (lane == 0) { prefetch_tm(&P.tm_wuk); prefetch_tm(j == 0 ? &P.tm_ckv : &P.tm_wuv); }
            int n = 4;
            auto acquire = [&](uint32_t bytes) -> uint32_t {
                mbar_wait(bar_xempty + (n & 3) * 8, ((n >> 2) - 1) & 1);
                mbar_expect_tx(bar_xfull + (n & 3) * 8, bytes);
                return (uint32_t)(n++ & 3);
            };
            if (lane == 0) {
#pragma unroll 1
                for (int k = 0; k < 2; k++) {
                    const uint32_t s = acquire(CH_BYTES);
                    tma2d_hint(sb + OFF_XR + s * CH_BYTES, &P.tm_wuk, h * 128 + 64 * k, 128 * j, bar_xfull + s * 8, pol);
                }
                if (j >= 2) {
                    mbar_wait(bar_trig, 0);
#pragma unroll 1
                    for (int k = 0; k < 4; k++) {
                        const uint32_t s = acquire(CH_BYTES);
                        tma2d_hint(sb + OFF_XR + s * CH_BYTES, &P.tm_wuv, h * 128 + 64 * (j - 2), 128 * k, bar_xfull + s * 8, pol);
                    }
                }
            }
            __syncwarp();
            if (j == 0) bar_sync(10, 64);
            if (lane == 0) {
                if (j == 0) wait_count(H.S->cntQ, ep * NCTA, QSLEEP);
                else if (j >= 2) { mbar_wait(bar_trig + 8, 0); wait_count(H.S->cntA, ep * 4 * A_SPLITS, FSLEEP); }
                asm volatile("fence.proxy.async.global;" ::: "memory");
                if (j == 0) {
#pragma unroll 1
                    for (int k = 0; k < 4; k++) {
                        const uint32_t s = acquire(CH_BYTES);
                        bulk_load_nh(sb + OFF_XR + s * CH_BYTES, &H.S->qabs[ab][2 * k][0][0][0][0][0], CH_BYTES, bar_xfull + s * 8);
                    }
#pragma unroll 1
                    for (int k = 0; k < A_TILES; k++) {
                        const uint32_t s = acquire(CH_BYTES);
                        tma3d_hint(sb + OFF_XR + s * CH_BYTES, &P.tm_ckv, 0, ab * 4096 + 16 * (k * A_SPLITS + asplit), 0, bar_xfull + s * 8, pol);
                    }
                } else if (j >= 2) {
#pragma unroll 1
                    for (int k = 0; k < 4; k++) {
                        const uint32_t s = acquire(CH_BYTES + A_SPLITS * 8);
                        bulk_load_nh(sb + OFF_XR + s * CH_BYTES, &H.S->pA[h][k][0][0], CH_BYTES, bar_xfull + s * 8);
                        bulk_load_nh(sb + OFF_MLA + k * A_SPLITS * 8, &H.S->mlA[h][k][0], A_SPLITS * 8, bar_xfull + s * 8);
                    }
                }
            }
            __syncwarp();
            mbar_wait(bar_trig + 16, 0);
            if (lane == 0) {
                prefetch_tm(&P.tm_wo[br]);
                wait_count(H.S->cntQ, ep * NCTA, QSLEEP);
                mbar_arrive(bar_xdone);
            }
        }
    } else if (warp < 4) {
        asm volatile("setmaxnreg.dec.sync.aligned.u32 88;");
        bar_sync(1, 512);
        const uint32_t ep = epoch();
        const bool valid = (t == (g >> 1));
        const bool odd = g & 1;
        const int r8 = lane & 7;
        const uint32_t koff = (warp * 16 + r8 + 8 * ((lane >> 3) & 1)) * 256 + (((lane >> 4) ^ r8) << 4);
        const uint32_t voff = (warp * 16 + r8 + 8 * (lane >> 4)) * 256 + ((((lane >> 3) & 1) ^ r8) << 4);
        int r = 0;
#pragma unroll 1
        for (;; r++) {
            const int sk = (2 * r) % RING, sv = sk + 1;
            const uint32_t ph = ((2 * r) / RING) & 1;
            unsigned char* mg = smem + OFF_MG + (r & 1) * MG_BYTES;
            if (!mbar_wait(bar_qfull + (r & 3) * 8, ph)) break;
            if (r == 0 && threadIdx.x == 0) TL(4);
            const int piece = reinterpret_cast<volatile int*>(smem + OFF_META)[r & 3];
            if (piece < 0) {
                mbar_wait(bar_mempty + (r & 1) * 8, ((r >> 1) - 1) & 1);
                if (lane == 0) { *reinterpret_cast<int*>(mg + 2048 + 144) = piece; mbar_arrive(bar_sfull + (r & 1) * 8); }
                break;
            }
            uint32_t qf[16];
#pragma unroll
            for (int u = 0; u < 16; u++) qf[u] = reinterpret_cast<const uint32_t*>(smem + OFF_QT + (r & 3) * 256)[4 * (u ^ g) + t];
            mbar_wait(bar_full + sk * 8, ph);
            const uint32_t ka = sb + OFF_RING + sk * CH_BYTES + koff;
            float c0[4] = {0.f, 0.f, 0.f, 0.f}, c1[4] = {0.f, 0.f, 0.f, 0.f};
#pragma unroll
            for (int s = 0; s < 8; s += 2) {
                uint32_t a[4], b[4];
                ldsm4(a, ka ^ (s << 5));
                ldsm4(b, ka ^ ((s + 1) << 5));
                mma(c0, a[0], a[1], a[2], a[3], qf[2 * s], qf[2 * s + 1]);
                mma(c1, b[0], b[1], b[2], b[3], qf[2 * s + 2], qf[2 * s + 3]);
            }
            float slo = odd ? c0[1] + c1[1] : c0[0] + c1[0];
            float shi = odd ? c0[3] + c1[3] : c0[2] + c1[2];
            if (lane == 0) mbar_arrive(bar_empty + sk * 8 + (__float_as_uint(slo) & H.zero));
            slo = bf16_round(bf16_round(slo) * SCALE);
            shi = bf16_round(bf16_round(shi) * SCALE);
            const float m = warp_max(valid ? fmaxf(slo, shi) : -INFINITY);
            const float plo = valid ? ex2((slo - m) * LOG2E) : 0.f;
            const float phi = valid ? ex2((shi - m) * LOG2E) : 0.f;
            if (r >= 2) mbar_wait(bar_mempty + (r & 1) * 8, ((r >> 1) - 1) & 1);
            if (valid) reinterpret_cast<float*>(mg + 2048)[warp * 8 + g] = plo + phi;
            if (lane == 0) { reinterpret_cast<float*>(mg + 2048 + 128)[warp] = m; *reinterpret_cast<int*>(mg + 2048 + 144) = piece; }
            __syncwarp();
            if (lane == 0) mbar_arrive(bar_sfull + (r & 1) * 8);
            const uint32_t b0 = odd ? pack_bf16(0.f, plo) : pack_bf16(plo, 0.f);
            const uint32_t b1 = odd ? pack_bf16(0.f, phi) : pack_bf16(phi, 0.f);
            mbar_wait(bar_full + sv * 8, ph);
            if (warp == 0) TL3(0, 0);
            const uint32_t va = sb + OFF_RING + sv * CH_BYTES + voff;
            float ev[8], od[8];
#pragma unroll
            for (int i = 0; i < 8; i++) {
                uint32_t a[4];
                float acc[4] = {0.f, 0.f, 0.f, 0.f};
                ldsm4t(a, va ^ (i << 5));
                mma(acc, a[0], a[1], a[2], a[3], b0, b1);
                ev[i] = acc[0] + acc[3]; od[i] = acc[1] + acc[2];
            }
#pragma unroll
            for (int i = 0; i < 8; i += 2) {
                ev[i] += __shfl_xor_sync(0xffffffffu, ev[i + 1], 1);
                od[i] += __shfl_xor_sync(0xffffffffu, od[i + 1], 1);
            }
#pragma unroll
            for (int i = 0; i < 8; i += 4) {
                ev[i] += __shfl_xor_sync(0xffffffffu, ev[i + 2], 2);
                od[i] += __shfl_xor_sync(0xffffffffu, od[i + 2], 2);
            }
            reinterpret_cast<float4*>(mg)[warp * 32 + lane] = make_float4(ev[0], od[0], ev[4], od[4]);
            __syncwarp();
            if (lane == 0) {
                mbar_arrive(bar_mfull + (r & 1) * 8);
                mbar_arrive(bar_empty + sv * 8 + ((__float_as_uint(ev[0]) | __float_as_uint(ev[4])) & H.zero));
            }
        }
        TL3(2, 0);
        {
            int lane2 = lane;
            asm volatile("" : "+r"(lane2));
            const int g2 = lane2 >> 2;
            uint16_t* outp = reinterpret_cast<uint16_t*>(P.out) + (2 * (lane2 & 1) + ((lane2 >> 1) & 1)) * 1024 + 512 * br + 64 * cbk + 16 * warp + ((g2 & 1) ? g2 + 7 : g2);
            const uint32_t aoff = (r8 + 8 * (lane2 >> 4)) * 128 + (((2 * warp + ((lane2 >> 3) & 1)) ^ r8) << 4);
            uint32_t a0 = sb + OFF_RING + ((2 * r) % RING) * CH_BYTES + aoff;
            uint32_t vp0 = sb + OFF_SS + (g2 & 3) * 288 + 8 * (lane2 & 3);
            float d[2][4];
#pragma unroll
            for (int u = 0; u < 2; u++) d[u][0] = d[u][1] = d[u][2] = d[u][3] = 0.f;
#pragma unroll 1
            for (int k = 0; k < 4; k++) {
                uint32_t wf[8][4];
                uint2 ob[8];
                const uint32_t vb = bar_vec + (k == 3 ? 8 : 0), wb = bar_wo + k * 8;
                auto load_w = [&]() {
#pragma unroll
                    for (int s = 0; s < 8; s++) ldsm4t(wf[s], a0 + s * 2048);
                };
                auto load_v = [&]() {
#pragma unroll
                    for (int s = 0; s < 8; s++)
                        asm volatile("ld.shared.v2.u32 {%0,%1}, [%2];" : "=r"(ob[s].x), "=r"(ob[s].y) : "r"(vp0 + 32 * s) : "memory");
                };
                auto mmas = [&]() {
#pragma unroll
                    for (int s = 0; s < 8; s++) mma(d[s & 1], wf[s][0], wf[s][1], wf[s][2], wf[s][3], ob[s].x, ob[s].y);
                };
                bool vfirst = false;
                if (k) {
#pragma unroll 1
                    for (uint32_t it = 0; it < SPIN_LIMIT * 16; it++) {
                        vfirst = mbar_test(vb, 0);
                        if (vfirst || mbar_test(wb, 0)) break;
                    }
                }
                if (vfirst) {
                    load_v();
                    if (warp == 0) TL3(8 + k, 0);
                    mbar_wait(wb, 0);
                    if (warp == 0) TL3(20 + k, 0);
                    load_w(); mmas();
                } else {
                    mbar_wait(wb, 0);
                    if (warp == 0) TL3(20 + k, 0);
                    load_w();
                    mbar_wait(vb, 0);
                    if (warp == 0) TL3(8 + k, 0);
                    load_v(); mmas();
                }
                const float e0 = (t & 2) ? d[0][1] + d[1][1] : d[0][0] + d[1][0], e1 = (t & 2) ? d[0][3] + d[1][3] : d[0][2] + d[1][2];
                const float rv = __shfl_xor_sync(0xffffffffu, (g & 1) ? e0 : e1, 4);
                red_bf2(outp, (g & 1) ? pack_bf16(rv, e1) : pack_bf16(e0, rv), k == 3);
                a0 = k == 1 ? sb + OFF_XR + 2 * CH_BYTES + aoff : a0 + CH_BYTES;
                vp0 += 4 * 288;
            }
            TL3(12, 0);
        }
    } else {
        asm volatile("setmaxnreg.inc.sync.aligned.u32 192;");
        const int x = warp - 4, tid = threadIdx.x - 128;
        bar_sync(1, 512);
        const uint32_t ep = epoch();
        const uint32_t tag = tag16(ep), par = ep & 1;
        uint32_t* qdst = &H.S->q[mat][tid >> 6][mat ? kperm(64 * cb + (tid & 63)) : 64 * cb + (tid & 63)];
        st_rlx(qdst, 0);
        if (j >= 2) st_rlx(&H.S->vec[0][h][tid >> 6][kperm(64 * (j - 2) + (tid & 63))], 0);
        if (tid < 128) st_rlx(&H.S->vec[1][h][j][tid], 0);
        if (tid < 16) reinterpret_cast<uint32_t*>(P.out)[bid * 16 + tid] = 0u;
        if (!mat) {
            st_rlx4(&H.S->pB[NPIECE - 512 + 8 * cb + x][lane * 4], par ^ 1, par ^ 1, par ^ 1, par ^ 1);
            if (lane < 2) st_rlx4(&H.S->mlB[NPIECE - 512 + 8 * cb + x][lane * 4], par ^ 1, par ^ 1, par ^ 1, par ^ 1);
        }
        const uint32_t xr = sb + OFF_XR;
        auto xwait = [&](int n) { mbar_wait(bar_xfull + (n & 3) * 8, (n >> 2) & 1); };
        auto xrel  = [&](int n, uint32_t dep) { if (lane == 0) mbar_arrive(bar_xempty + (n & 3) * 8 + (dep & H.zero)); };
        float* red = reinterpret_cast<float*>(smem + OFF_SS + 8448);
        {
            uint32_t w[4][4][4], xb[4][2];
#pragma unroll
            for (int s = 0; s < 4; s++) {
                const uint32_t* X = reinterpret_cast<const uint32_t*>(smem + OFF_X) + (g & 3) * 256 + 32 * x + 8 * s + t;
                xb[s][0] = X[0]; xb[s][1] = X[4];
            }
            xwait(x >> 1);
            const uint32_t dep = load_wT<4>(w, xr + x * 8192, lane);
            float acc[4][4];
#pragma unroll
            for (int u = 0; u < 4; u++) acc[u][0] = acc[u][1] = acc[u][2] = acc[u][3] = 0.f;
#pragma unroll
            for (int s = 0; s < 4; s++)
#pragma unroll
                for (int mt = 0; mt < 4; mt++) mma(acc[mt], w[s][mt][0], w[s][mt][1], w[s][mt][2], w[s][mt][3], xb[s][0], xb[s][1]);
#pragma unroll
            for (int n = 0; n < 4; n++) xrel(n, dep);
            if (t < 2) {
#pragma unroll
                for (int mt = 0; mt < 4; mt++) {
                    float* r0 = red + (x * 4 + 2 * t) * 64 + 16 * mt + g;
                    r0[0] = acc[mt][0]; r0[8] = acc[mt][2]; r0[64] = acc[mt][1]; r0[72] = acc[mt][3];
                }
            }
            bar_sync(2, 256);
            float s = 0.f;
#pragma unroll
            for (int i = 0; i < 8; i++) s += red[i * 256 + tid];
            st_rlx(qdst, (pack_bf16(0.f, s) & 0xffff0000u) | tag);
        }
        if (tid == 0) TL(6);
        {
            uint32_t w[8][4];
            const int r8 = lane & 7;
            const uint32_t a0 = xr + (16 * x + r8 + 8 * ((lane >> 3) & 1)) * 128 + (((lane >> 4) ^ r8) << 4);
#pragma unroll
            for (int hf = 0; hf < 2; hf++) {
                xwait(4 + hf);
                uint32_t dep = 0;
#pragma unroll
                for (int ks = 0; ks < 4; ks++) { ldsm4(w[4 * hf + ks], (a0 ^ (ks << 5)) + hf * CH_BYTES); dep |= w[4 * hf + ks][0]; }
                xrel(4 + hf, dep);
            }
            if (x < 4) gather128(&H.S->q[1][x][h * 128], tag, smem + OFF_OA + x * 288, lane, QD1);
            bar_sync(2, 256);
            float c[4] = {0.f, 0.f, 0.f, 0.f};
#pragma unroll
            for (int i = 0; i < 8; i++) {
                const uint2 b = *reinterpret_cast<const uint2*>(smem + OFF_OA + (g & 3) * 288 + (16 * i + 4 * t) * 2);
                mma(c, w[i][0], w[i][1], w[i][2], w[i][3], b.x, b.y);
            }
            uint16_t* stg = reinterpret_cast<uint16_t*>(smem + OFF_SS);
            if (t < 2) {
                const int ks = x & 3;
#pragma unroll
                for (int q = 0; q < 4; q++) {
                    const int b = 2 * t + (q & 1), rg = q >> 1;
                    const float vh = bf16_round(c[q]);
                    const int o = b * 256 + (x >> 2) * 128 + (ks >> 1) * 32 + (g >> 1) * 8 + (ks & 1) * 4 + rg * 2 + (g & 1);
                    stg[o]      = (uint16_t)(__float_as_uint(vh) >> 16);
                    stg[o + 64] = (uint16_t)pack_bf16(c[q] - vh, 0.f);
                }
            }
            bar_sync(2, 256);
            if (tid < 128) {
                const uint4 val = reinterpret_cast<const uint4*>(stg)[tid];
                *reinterpret_cast<uint4*>(&H.S->qabs[tid >> 5][2 * j + ((tid >> 4) & 1)][(tid >> 3) & 1][h >> 3][(tid >> 2) & 1][(h & 7) * 4 + (tid & 3)][0]) = val;
            }
            bar_sync(2, 256);
            if (tid == 0) { add_rel(H.S->cntQ); TL(7); }
            if (j == 0 && x == 0) bar_arrive(10, 64);
        }
        if (j == 0) {
            uint32_t qf[2][4][8];
#pragma unroll
            for (int k = 0; k < 4; k++) {
                xwait(6 + k);
                uint32_t dep = 0;
                if (k == (x >> 1)) {
                    const unsigned char* qp = smem + OFF_XR + ((6 + k) & 3) * CH_BYTES + (x & 1) * 8192 + lane * 16;
#pragma unroll
                    for (int i = 0; i < 16; i++) {
                        const uint4 a = *reinterpret_cast<const uint4*>(qp + i * 512);
                        uint32_t* d = &qf[i >> 3][(i >> 1) & 3][4 * (i & 1)];
                        d[0] = a.x; d[1] = a.y; d[2] = a.z; d[3] = a.w;
                        dep |= a.x;
                    }
                }
                xrel(6 + k, dep);
            }
            if (tid == 0) TL(8);
            float acc[4][4][4];
#pragma unroll
            for (int a = 0; a < 4; a++)
#pragma unroll
                for (int b = 0; b < 4; b++) acc[a][b][0] = acc[a][b][1] = acc[a][b][2] = acc[a][b][3] = 0.f;
            float m = -INFINITY, l = 0.f;
            const int r8 = lane & 7;
            const uint32_t koff = x * 2048 + (r8 + 8 * ((lane >> 3) & 1)) * 128 + (((lane >> 4) ^ r8) << 4);
            const uint32_t voff = x * 2048 + (r8 + 8 * (lane >> 4)) * 128 + ((((lane >> 3) & 1) ^ r8) << 4);
            const int sh = tid >> 3, skp = tid & 7;
#define CK0
#define CK1(v)
            for (int n = 10; n < 10 + A_TILES; n++) {
                CK0
                xwait(n);
                CK1(cw)
                const uint32_t base = xr + (n & 3) * CH_BYTES;
                float S[4][4];
#pragma unroll
                for (int nt = 0; nt < 4; nt++) S[nt][0] = S[nt][1] = S[nt][2] = S[nt][3] = 0.f;
#pragma unroll
                for (int ks = 0; ks < 4; ks++) {
                    uint32_t a[4];
                    ldsm4(a, base + (koff ^ (ks << 5)));
#pragma unroll
                    for (int nt = 0; nt < 4; nt++) mma(S[nt], a[0], a[1], a[2], a[3], qf[1][nt][2 * ks], qf[1][nt][2 * ks + 1]);
#pragma unroll
                    for (int nt = 0; nt < 4; nt++) mma(S[nt], a[0], a[1], a[2], a[3], qf[0][nt][2 * ks], qf[0][nt][2 * ks + 1]);
                }
#pragma unroll
                for (int nt = 0; nt < 4; nt++) {
                    unsigned char* sp = smem + OFF_SS + (x * 32 + 8 * nt + 2 * t) * 80 + 8 * g;
                    *reinterpret_cast<float2*>(sp) = make_float2(S[nt][0], S[nt][2]);
                    *reinterpret_cast<float2*>(sp + 80) = make_float2(S[nt][1], S[nt][3]);
                }
                bar_sync(2, 256);
                CK1(c1)
                float s0 = 0.f, s1 = 0.f;
#pragma unroll
                for (int w = 0; w < 8; w++) {
                    const float2 v = *reinterpret_cast<const float2*>(smem + OFF_SS + (w * 32 + sh) * 80 + 8 * skp);
                    s0 += v.x; s1 += v.y;
                }
                s0 = bf16_round(bf16_round(s0) * SCALE);
                s1 = bf16_round(bf16_round(s1) * SCALE);
                float mx = fmaxf(s0, s1);
                mx = fmaxf(mx, __shfl_xor_sync(0xffffffffu, mx, 1));
                mx = fmaxf(mx, __shfl_xor_sync(0xffffffffu, mx, 2));
                mx = fmaxf(mx, __shfl_xor_sync(0xffffffffu, mx, 4));
                mx = fmaxf(mx, m);
                const float al = ex2((m - mx) * LOG2E);
                m = mx;
                const float p0 = ex2((s0 - m) * LOG2E), p1 = ex2((s1 - m) * LOG2E);
                l = l * al + p0 + p1;
                {
                    const uint32_t pp = pack_bf16(p0, p1);
                    uint16_t* dst = reinterpret_cast<uint16_t*>(smem + OFF_SP) + sh * 16 + kperm(skp);
                    dst[0] = (uint16_t)pp; dst[2] = (uint16_t)(pp >> 16);
                }
                if (skp == 0) reinterpret_cast<float*>(smem + OFF_ALPHA)[sh] = al;
                bar_sync(2, 256);
                CK1(c2)
                uint2 pb[4];
#pragma unroll
                for (int nt = 0; nt < 4; nt++) {
                    pb[nt] = *reinterpret_cast<const uint2*>(smem + OFF_SP + (8 * nt + g) * 32 + 8 * t);
                    const float2 a2 = *reinterpret_cast<const float2*>(smem + OFF_ALPHA + (8 * nt + 2 * t) * 4);
#pragma unroll
                    for (int mt = 0; mt < 4; mt++) {
                        acc[mt][nt][0] *= a2.x; acc[mt][nt][1] *= a2.y; acc[mt][nt][2] *= a2.x; acc[mt][nt][3] *= a2.y;
                    }
                }
                uint32_t dep = 0;
#pragma unroll
                for (int mt = 0; mt < 4; mt++) {
                    uint32_t a[4];
                    ldsm4t(a, base + (voff ^ (mt << 5)));
                    dep |= a[0];
#pragma unroll
                    for (int nt = 0; nt < 4; nt++) mma(acc[mt][nt], a[0], a[1], a[2], a[3], pb[nt].x, pb[nt].y);
                }
                xrel(n, dep);
                CK1(c3)
            }
#pragma unroll
            for (int nt = 0; nt < 4; nt++)
#pragma unroll
                for (int e = 0; e < 2; e++) {
                    float* dst = &H.S->pA[8 * nt + 2 * t + e][ab][asplit][64 * x + 4 * g];
                    *reinterpret_cast<float4*>(dst)      = make_float4(acc[0][nt][e], acc[0][nt][2 + e], acc[1][nt][e], acc[1][nt][2 + e]);
                    *reinterpret_cast<float4*>(dst + 32) = make_float4(acc[2][nt][e], acc[2][nt][2 + e], acc[3][nt][e], acc[3][nt][2 + e]);
                }
            l += __shfl_xor_sync(0xffffffffu, l, 1);
            l += __shfl_xor_sync(0xffffffffu, l, 2);
            l += __shfl_xor_sync(0xffffffffu, l, 4);
            if (skp == 0) H.S->mlA[sh][ab][asplit] = make_float2(m, l);
            bar_sync(2, 256);
            if (tid == 0) { add_rel(H.S->cntA); TL(9); }
        } else if (j >= 2) {
            uint32_t wv[4][4][4];
#pragma unroll
            for (int k = 0; k < 4; k++) {
                xwait(6 + k);
                uint32_t dep = 0;
                if (k == (x >> 1)) dep = load_wT<4>(wv, xr + ((6 + k) & 3) * CH_BYTES + (x & 1) * 8192, lane);
                xrel(6 + k, dep);
            }
            {
                const int b = tid >> 6, xx = (tid >> 3) & 7, gg = tid & 7;
                xwait(10 + b);
                if (tid == 0) TL(8);
                const float2* mlp = reinterpret_cast<const float2*>(smem + OFF_MLA) + b * A_SPLITS;
                float mm = -INFINITY, ll = 0.f;
#pragma unroll
                for (int s = 0; s < A_SPLITS; s++) mm = fmaxf(mm, mlp[s].x);
#pragma unroll
                for (int s = 0; s < A_SPLITS; s++) ll += mlp[s].y * ex2((mlp[s].x - mm) * LOG2E);
                const float inv = 1.f / ll;
                float cl[8];
#pragma unroll
                for (int e = 0; e < 8; e++) cl[e] = 0.f;
                const float* src = reinterpret_cast<const float*>(smem + OFF_XR + ((10 + b) & 3) * CH_BYTES) + 64 * xx + 4 * gg;
#pragma unroll
                for (int s = 0; s < A_SPLITS; s++) {
                    const float wt = ex2((mlp[s].x - mm) * LOG2E) * inv;
                    const float4 a = *reinterpret_cast<const float4*>(src + s * 512), c = *reinterpret_cast<const float4*>(src + s * 512 + 32);
                    cl[0] += wt * a.x; cl[1] += wt * a.y; cl[2] += wt * a.z; cl[3] += wt * a.w;
                    cl[4] += wt * c.x; cl[5] += wt * c.y; cl[6] += wt * c.z; cl[7] += wt * c.w;
                }
                uint16_t* hi = reinterpret_cast<uint16_t*>(smem + OFF_SS + b * 1056);
                uint16_t* lo = reinterpret_cast<uint16_t*>(smem + OFF_SS + (b + 4) * 1056);
#pragma unroll
                for (int e = 0; e < 8; e++) {
                    const int c = kperm(64 * xx + 8 * e + gg);
                    const float vh = bf16_round(cl[e]);
                    hi[c] = (uint16_t)(__float_as_uint(vh) >> 16);
                    lo[c] = (uint16_t)pack_bf16(cl[e] - vh, 0.f);
                }
                bar_sync(2, 256);
#pragma unroll
                for (int k = 0; k < 4; k++) xrel(10 + k, __float_as_uint(cl[0]) | __float_as_uint(cl[4]));
            }
            {
                float acc[4][4];
#pragma unroll
                for (int u = 0; u < 4; u++) acc[u][0] = acc[u][1] = acc[u][2] = acc[u][3] = 0.f;
#pragma unroll
                for (int s = 0; s < 4; s++) {
                    const uint2 b = *reinterpret_cast<const uint2*>(smem + OFF_SS + g * 1056 + (64 * x + 16 * s + 4 * t) * 2);
#pragma unroll
                    for (int mt = 0; mt < 4; mt++) mma(acc[mt], wv[s][mt][0], wv[s][mt][1], wv[s][mt][2], wv[s][mt][3], b.x, b.y);
                }
#pragma unroll
                for (int mt = 0; mt < 4; mt++)
#pragma unroll
                    for (int e = 0; e < 4; e++) acc[mt][e] += __shfl_xor_sync(0xffffffffu, acc[mt][e], 2);
                if (t < 2) {
#pragma unroll
                    for (int mt = 0; mt < 4; mt++) {
                        float* r0 = red + (x * 4 + 2 * t) * 64 + 16 * mt + g;
                        r0[0] = acc[mt][0]; r0[8] = acc[mt][2]; r0[64] = acc[mt][1]; r0[72] = acc[mt][3];
                    }
                }
            }
            bar_sync(2, 256);
            {
                float s = 0.f;
#pragma unroll
                for (int i = 0; i < 8; i++) s += red[i * 256 + tid];
                st_rlx(&H.S->vec[0][h][tid >> 6][kperm(64 * (j - 2) + (tid & 63))], (pack_bf16(0.f, s) & 0xffff0000u) | tag);
            }
            if (tid == 0) TL(9);
        }
        {
            __syncwarp();
            if (lane == 0) mbar_arrive(bar_xdone);
#pragma unroll 1
            for (uint32_t pass = H.zero; pass < 2; pass++) {
                if (pass == br) {
                    mbar_wait(br ? bar_cmb + 8 : bar_trig + 16, 0);
#pragma unroll 1
                    for (int u = 2 * x; u < 2 * x + 2; u++)
                        if (u < 15 || hl < HURG) gather128(&H.S->vec[br][hp + 8 * (u >> 2)][u & 3][0], tag, smem + OFF_SS + u * 288, lane, QD1);
                    __syncwarp();
                    if (lane == 0) { mbar_arrive(bar_vec); if (hl < HURG) mbar_arrive(bar_vec + 8); }
                    TL3(13, 0);
                    if (tid == 0) { H.S->epoch[bid] = ep; TL(10); }
                }
                if (pass ? hl >= HURG : (j < 3 || h < HURG)) {
                    const int pr = pass ? 96 + hl : 32 * j + h;
                    const uint32_t* rp = &H.S->pB[64 * pr + 8 * x][lane * 4];
                    const uint32_t* sp = &H.S->mlB[64 * pr + 8 * x + (lane & 7)][0];
                    uint4 v[8], sv;
                    mbar_wait(bar_cmb + pass * 16, 0);
                    TL3(5, 0);
                    if (lane == 0) {
                        mbar_expect_tx(bar_gat + x * 8, 4096 + 256);
                        bulk_load_nh(xr + x * 4096, rp, 4096, bar_gat + x * 8);
                        bulk_load_nh(sb + OFF_ST + x * 256, sp, 256, bar_gat + x * 8);
                    }
                    __syncwarp();
                    mbar_wait(bar_gat + x * 8, pass);
                    TL3(15, 0);
                    sv = lds128(sb + OFF_ST + x * 256 + (lane & 7) * 32);
#pragma unroll
                    for (int i = 0; i < 8; i++) v[i] = lds128(xr + x * 4096 + i * 512 + lane * 16);
                    float mx, ll, wt[8];
#pragma unroll 1
                    for (uint32_t it = 0;; it++) {
                        uint32_t bad[9];
#pragma unroll
                        for (int i = 0; i < 8; i++) bad[i] = untagged(v[i], par);
                        bad[8] = untagged(sv, par);
                        const uint32_t anyb = or3(or3(bad[0], bad[1], bad[2]), or3(bad[3], bad[4], bad[5]), or3(bad[6], bad[7], bad[8]));
                        const float m0 = __uint_as_float(sv.y);
                        mx = warp_max(m0);
                        const float w0 = ex2((m0 - mx) * LOG2E);
                        ll = w0 * __uint_as_float(sv.x);
                        const float l4 = __shfl_xor_sync(0xffffffffu, ll, 4);
#pragma unroll
                        for (int i = 0; i < 8; i++) wt[i] = __shfl_sync(0xffffffffu, w0, i);
                        ll += l4;
                        ll += __shfl_xor_sync(0xffffffffu, ll, 2);
                        if (!__any_sync(0xffffffffu, anyb & 1) || it >= SPIN_LIMIT) break;
                        uint32_t mask = 0;
#pragma unroll
                        for (int i = 0; i < 9; i++) mask |= (bad[i] & 1) << i;
                        const uint32_t pend = __reduce_or_sync(0xffffffffu, mask);
                        ld_rlx2x64_if(sv, sp, pend & 256);
#pragma unroll
                        for (int i = 0; i < 8; i++) ld_rlx2x64_if(v[i], rp + i * 128, pend & (1 << i));
                    }
                    ll += __shfl_xor_sync(0xffffffffu, ll, 1);
                    float4 acc = make_float4(0.f, 0.f, 0.f, 0.f), acd = acc;
#pragma unroll
                    for (int i = 0; i < 8; i += 2) {
                        acc.x += wt[i] * __uint_as_float(v[i].x); acc.y += wt[i] * __uint_as_float(v[i].y);
                        acc.z += wt[i] * __uint_as_float(v[i].z); acc.w += wt[i] * __uint_as_float(v[i].w);
                        acd.x += wt[i + 1] * __uint_as_float(v[i + 1].x); acd.y += wt[i + 1] * __uint_as_float(v[i + 1].y);
                        acd.z += wt[i + 1] * __uint_as_float(v[i + 1].z); acd.w += wt[i + 1] * __uint_as_float(v[i + 1].w);
                    }
                    acc.x += acd.x; acc.y += acd.y; acc.z += acd.z; acc.w += acd.w;
                    TL3(6, 0);
                    if (lane == 0) reinterpret_cast<float2*>(red + 1024)[x] = make_float2(mx, ll);
                    reinterpret_cast<float4*>(red)[tid] = acc;
                    const int d = kperm(16 * ((tid >> 2) & 3) + 8 * (tid & 1) + 64 * ((tid >> 1) & 1) + ((tid >> 4) & 7));
                    uint32_t od = sb + OFF_SS + 15 * 288 + 2 * d, ra = sb + OFF_SS + 8448;
                    asm volatile("" : "+r"(od), "+r"(ra));
                    bar_sync(2, 256);
                    if (x < 4) {
                        uint4 st[4];
                        float r[8];
#pragma unroll
                        for (int i = 0; i < 4; i++) st[i] = lds128(ra + 4096 + 16 * i);
#pragma unroll
                        for (int i = 0; i < 8; i++) r[i] = lds32(ra + 512 * i + 4 * tid);
                        float m2[4];
#pragma unroll
                        for (int i = 0; i < 4; i++) m2[i] = fmaxf(__uint_as_float(st[i].x), __uint_as_float(st[i].z));
                        const float mm = fmaxf(fmaxf(m2[0], m2[1]), fmaxf(m2[2], m2[3]));
                        float s0 = 0.f, s1 = 0.f, l0 = 0.f, l1 = 0.f;
#pragma unroll
                        for (int i = 0; i < 4; i++) {
                            const float f0 = ex2((__uint_as_float(st[i].x) - mm) * LOG2E), f1 = ex2((__uint_as_float(st[i].z) - mm) * LOG2E);
                            s0 += f0 * r[2 * i]; s1 += f1 * r[2 * i + 1];
                            l0 += f0 * __uint_as_float(st[i].y); l1 += f1 * __uint_as_float(st[i].w);
                        }
                        float inv;
                        asm("rcp.approx.ftz.f32 %0, %1;" : "=f"(inv) : "f"(l0 + l1));
                        const uint32_t ob = pack_bf16((s0 + s1) * inv, 0.f);
                        if (pass) asm volatile("st.shared.u16 [%0], %1;" :: "r"(od), "h"((uint16_t)ob) : "memory");
                        else st_rlx(&H.S->vec[1][h][j][d], (ob << 16) | tag);
                    }
                    __syncwarp();
                    if (pass && lane == 0) mbar_arrive(bar_vec + 8);
                    TL3(7, 0);
                    if (!pass) bar_sync(2, 256);
                }
            }
        }
    }
}

typedef CUresult (*EncodeFn)(CUtensorMap*, CUtensorMapDataType, cuuint32_t, void*, const cuuint64_t*, const cuuint64_t*,
                             const cuuint32_t*, const cuuint32_t*, CUtensorMapInterleave, CUtensorMapSwizzle,
                             CUtensorMapL2promotion, CUtensorMapFloatOOBfill);

void encode2d(EncodeFn fn, CUtensorMap* tm, void* ptr, uint64_t cols, uint64_t rows, uint32_t box_rows) {
    const cuuint64_t dims[2] = {cols, rows};
    const cuuint64_t strides[1] = {cols * 2};
    const cuuint32_t box[2] = {64, box_rows};
    const cuuint32_t es[2] = {1, 1};
    fn(tm, CU_TENSOR_MAP_DATA_TYPE_BFLOAT16, 2, ptr, dims, strides, box, es, CU_TENSOR_MAP_INTERLEAVE_NONE,
       CU_TENSOR_MAP_SWIZZLE_128B, CU_TENSOR_MAP_L2_PROMOTION_NONE, CU_TENSOR_MAP_FLOAT_OOB_FILL_NONE);
}

}

extern "C" void kernel_launch(void* const* d_in, const int* in_sizes, int n_in, void* d_out, int out_size) {
    (void)in_sizes; (void)n_in; (void)out_size;
    static EncodeFn encode = nullptr;
    static Scratch* scratch = nullptr;
    if (!encode) {
        cudaFuncSetAttribute(fused_decode_kernel, cudaFuncAttributeMaxDynamicSharedMemorySize, SMEM_BYTES + SMEM_EXTRA);
        void* fn = nullptr;
        cudaDriverEntryPointQueryResult qr;
        cudaGetDriverEntryPoint("cuTensorMapEncodeTiled", &fn, cudaEnableDefault, &qr);
        encode = (EncodeFn)fn;
        void* sp = nullptr;
        cudaGetSymbolAddress(&sp, g_scratch);
        scratch = (Scratch*)sp;
    }
    Params p;
    encode2d(encode, &p.tm_wq[0], d_in[9], 4096, 512, 128);
    encode2d(encode, &p.tm_wq[1], d_in[2], 4096, 512, 128);
    encode2d(encode, &p.tm_wuk,   d_in[3], 4096, 512, 128);
    encode2d(encode, &p.tm_wuv,   d_in[4], 4096, 512, 128);
    encode2d(encode, &p.tm_wo[1], d_in[10], 512, 4096, 128);
    encode2d(encode, &p.tm_wo[0], d_in[5], 512, 4096, 128);
    {
        const cuuint64_t dims[3] = {64, 16384, 8};
        const cuuint64_t strides[2] = {1024, 128};
        const cuuint32_t box[3] = {64, 16, 8};
        const cuuint32_t es[3] = {1, 1, 1};
        encode(&p.tm_ckv, CU_TENSOR_MAP_DATA_TYPE_BFLOAT16, 3, d_in[1], dims, strides, box, es, CU_TENSOR_MAP_INTERLEAVE_NONE,
               CU_TENSOR_MAP_SWIZZLE_128B, CU_TENSOR_MAP_L2_PROMOTION_NONE, CU_TENSOR_MAP_FLOAT_OOB_FILL_NONE);
    }
    p.wo[0] = (const __nv_bfloat16*)d_in[5];
    p.wo[1] = (const __nv_bfloat16*)d_in[10];
    p.out = (__nv_bfloat16*)d_out;
    Hot hp;
    hp.kp = (const char*)d_in[7];
    hp.vp = (const char*)d_in[8];
    hp.S = scratch;
    hp.x[0] = (const __nv_bfloat16*)d_in[6];
    hp.x[1] = (const __nv_bfloat16*)d_in[0];
    hp.zero = 0;
    hp.never = 0;
    cudaLaunchConfig_t cfg = {};
    cfg.gridDim = dim3(NCTA);
    cfg.blockDim = dim3(NTHREADS);
    cfg.dynamicSmemBytes = SMEM_BYTES + SMEM_EXTRA;
    cfg.stream = cudaStreamPerThread;
    cudaLaunchAttribute at[1];
    at[0].id = cudaLaunchAttributeCooperative;
    at[0].val.cooperative = 1;
    cfg.attrs = at;
    cfg.numAttrs = 1;
    cudaLaunchKernelEx(&cfg, fused_decode_kernel, hp, p);
}
```

```cpp
#include <cuda_runtime.h>
#include <cuda.h>
#include <cuda_bf16.h>
#include <stdint.h>

namespace {

constexpr int NCTA      = 128;
constexpr int NTHREADS  = 512;
constexpr int CH_BYTES  = 16384;
constexpr int NPIECE    = 128 * 64;
constexpr int RING      = 8;
#define PFV 10240
#define WIN 3
#define DL0 3250
#define DLS 1000
#define NB2 4650
#define NBS 1300
#define DLR 18
#define HS 31
#define XS 224
#define TG 5700
#define LAG 192
#define LAG2 96
#define LAG1 192
#define HURG 24
#define FSLEEP 600
#define QSLEEP 400
#define QD0 600
#define QD1 100
#define TRIG0 (20 * 128)
#define TRIG1 (32 * 128)
#define TRIG2 (50 * 128)
constexpr int SMEM_EXTRA = 0;
constexpr int A_SPLITS  = 8;
constexpr int A_TILES   = 4096 / A_SPLITS / 16;

constexpr int OFF_RING  = 0;
constexpr int OFF_XR    = OFF_RING + RING * CH_BYTES;
constexpr int OFF_SS    = OFF_XR + 4 * CH_BYTES;
constexpr int OFF_SP    = OFF_SS + 8 * 32 * 80;
constexpr int OFF_ALPHA = OFF_SP + 1024;
constexpr int OFF_OA    = OFF_ALPHA + 128;
constexpr int OFF_ST    = OFF_OA + 4 * 288;
constexpr int OFF_MLA   = OFF_ST + 64 * 32;
constexpr int OFF_QT    = OFF_MLA + 4 * A_SPLITS * 8;
constexpr int MG_BYTES  = 2048 + 128 + 32;
constexpr int OFF_MG    = OFF_QT + 4 * 256;
constexpr int OFF_META  = OFF_MG + 2 * MG_BYTES;
constexpr int OFF_EP    = OFF_META + 16;
constexpr int OFF_X     = OFF_SS + 4096;
constexpr int OFF_BAR   = OFF_EP + 16;
constexpr int NBAR      = 2 * RING + 8 + 2 + 3 + 4 + 3 + 1 + 8 + 8 + 2 + 2 + 2 + 1;
constexpr int I_INI     = 2 * RING + 8 + 2 + 3 + 4 + 3;
constexpr int SMEM_BYTES = OFF_BAR + NBAR * 8;

constexpr float LOG2E = 1.4426950408889634f;
constexpr float SCALE = 0.08838834764831845f;
constexpr uint32_t SPIN_LIMIT = 1u << 20;

struct Scratch {
    uint32_t ticket[2][64];
    uint32_t epoch[NCTA];
    uint32_t cntQ[64], cntA[64];
    float2   mlA[32][4][A_SPLITS];
    uint32_t vec[2][32][4][128];
    uint32_t q[2][4][4096];
    uint16_t qabs[4][8][2][4][2][32][8];
    float    pA[32][4][A_SPLITS][512];
    uint32_t pB[NPIECE][128];
    uint32_t mlB[NPIECE][8];
};
__device__ __align__(128) Scratch g_scratch;
#define TL(i) do {} while (0)
#define TL3(i, dep) do {} while (0)
#define TLG(i) do {} while (0)
#define TL2(i) do {} while (0)

struct Hot {
    const char *kp, *vp;
    Scratch* S;
    const __nv_bfloat16* x[2];
    uint32_t zero;
    uint32_t never;
};
struct Params {
    CUtensorMap tm_wq[2];
    CUtensorMap tm_wuk, tm_wuv;
    CUtensorMap tm_wo[2];
    CUtensorMap tm_ckv;
    const __nv_bfloat16* wo[2];
    __nv_bfloat16* out;
};

__device__ __forceinline__ void mbar_init(uint32_t bar, uint32_t cnt) {
    asm volatile("mbarrier.init.shared::cta.b64 [%0], %1;" :: "r"(bar), "r"(cnt) : "memory");
}
__device__ __forceinline__ void mbar_expect_tx(uint32_t bar, uint32_t bytes) {
    asm volatile("mbarrier.arrive.expect_tx.shared::cta.b64 _, [%0], %1;" :: "r"(bar), "r"(bytes) : "memory");
}
__device__ __forceinline__ void mbar_arrive(uint32_t bar) {
    asm volatile("mbarrier.arrive.shared::cta.b64 _, [%0];" :: "r"(bar) : "memory");
}
template <uint32_t LIMIT = SPIN_LIMIT>
__device__ __forceinline__ bool mbar_wait(uint32_t bar, uint32_t parity) {
    uint32_t done, it = 0;
    do {
        asm volatile("{\n.reg .pred p;\nmbarrier.try_wait.parity.shared::cta.b64 p, [%1], %2;\nselp.u32 %0, 1, 0, p;\n}"
                     : "=r"(done) : "r"(bar), "r"(parity) : "memory");
        if (++it > LIMIT) break;
    } while (!done);
    return done;
}
__device__ __forceinline__ void bulk_load(uint32_t dst, const void* src, uint32_t bytes, uint32_t bar, uint64_t pol) {
    asm volatile("cp.async.bulk.shared::cluster.global.mbarrier::complete_tx::bytes.L2::cache_hint [%0], [%1], %2, [%3], %4;"
                 :: "r"(dst), "l"(src), "r"(bytes), "r"(bar), "l"(pol) : "memory");
}
__device__ __forceinline__ uint64_t policy_evict_first() {
    uint64_t pol;
    asm volatile("createpolicy.fractional.L2::evict_first.b64 %0, 1.0;" : "=l"(pol));
    return pol;
}
__device__ __forceinline__ void bar_sync(int id, int n)   { asm volatile("bar.sync %0, %1;" :: "r"(id), "r"(n) : "memory"); }
__device__ __forceinline__ void bar_arrive(int id, int n) { asm volatile("bar.arrive %0, %1;" :: "r"(id), "r"(n) : "memory"); }
__device__ __forceinline__ void ldsm4(uint32_t (&r)[4], uint32_t addr) {
    asm volatile("ldmatrix.sync.aligned.m8n8.x4.shared.b16 {%0,%1,%2,%3}, [%4];"
                 : "=r"(r[0]), "=r"(r[1]), "=r"(r[2]), "=r"(r[3]) : "r"(addr) : "memory");
}
__device__ __forceinline__ void ldsm4t(uint32_t (&r)[4], uint32_t addr) {
    asm volatile("ldmatrix.sync.aligned.m8n8.x4.trans.shared.b16 {%0,%1,%2,%3}, [%4];"
                 : "=r"(r[0]), "=r"(r[1]), "=r"(r[2]), "=r"(r[3]) : "r"(addr) : "memory");
}
__device__ __forceinline__ void mma(float (&c)[4], uint32_t a0, uint32_t a1, uint32_t a2, uint32_t a3, uint32_t b0, uint32_t b1) {
    asm volatile("mma.sync.aligned.m16n8k16.row.col.f32.bf16.bf16.f32 {%0,%1,%2,%3}, {%4,%5,%6,%7}, {%8,%9}, {%0,%1,%2,%3};"
                 : "+f"(c[0]), "+f"(c[1]), "+f"(c[2]), "+f"(c[3])
                 : "r"(a0), "r"(a1), "r"(a2), "r"(a3), "r"(b0), "r"(b1));
}
__device__ __forceinline__ uint32_t prmt(uint32_t a, uint32_t b, uint32_t s) {
    uint32_t r; asm("prmt.b32 %0, %1, %2, %3;" : "=r"(r) : "r"(a), "r"(b), "r"(s)); return r;
}
__device__ __forceinline__ uint32_t pack_bf16(float lo, float hi) {
    uint32_t r; asm("cvt.rn.bf16x2.f32 %0, %1, %2;" : "=r"(r) : "f"(hi), "f"(lo)); return r;
}
__device__ __forceinline__ float bf16_round(float v) { return __uint_as_float(pack_bf16(0.f, v) & 0xffff0000u); }
__device__ __forceinline__ float ex2(float x) { float r; asm("ex2.approx.ftz.f32 %0, %1;" : "=f"(r) : "f"(x)); return r; }
__device__ __forceinline__ uint4 ld_rlx4(const void* p) {
    uint4 v;
    asm volatile("ld.relaxed.gpu.global.v4.u32 {%0,%1,%2,%3}, [%4];" : "=r"(v.x), "=r"(v.y), "=r"(v.z), "=r"(v.w) : "l"(p) : "memory");
    return v;
}
__device__ __forceinline__ uint32_t ld_acq(const void* p) {
    uint32_t v; asm volatile("ld.acquire.gpu.global.u32 %0, [%1];" : "=r"(v) : "l"(p) : "memory"); return v;
}
__device__ __forceinline__ void st_rlx(void* p, uint32_t v) { asm volatile("st.relaxed.gpu.global.u32 [%0], %1;" :: "l"(p), "r"(v) : "memory"); }
__device__ __forceinline__ void st_rlx4(void* p, uint32_t a, uint32_t b, uint32_t c, uint32_t d) {
    asm volatile("st.relaxed.gpu.global.v4.u32 [%0], {%1,%2,%3,%4};" :: "l"(p), "r"(a), "r"(b), "r"(c), "r"(d) : "memory");
}
__device__ __forceinline__ float warp_max(float v) {
    int k = __float_as_int(v);
    k ^= (k >> 31) & 0x7fffffff;
    k = __reduce_max_sync(0xffffffffu, k);
    k ^= (k >> 31) & 0x7fffffff;
    return __int_as_float(k);
}
__device__ __forceinline__ uint32_t tagf(float v, uint32_t par) { return (__float_as_uint(v) & ~1u) | par; }
__device__ __forceinline__ void wait_count(const uint32_t* c, uint32_t val, uint32_t sleep) {
#pragma unroll 1
    for (uint32_t it = 0; it < SPIN_LIMIT && ld_acq(c) != val; it++) __nanosleep(sleep);
}
__device__ __forceinline__ uint32_t take_ticket(uint32_t* c) {
    uint32_t v; asm volatile("atom.relaxed.gpu.global.add.u32 %0, [%1], 1;" : "=r"(v) : "l"(c) : "memory"); return v;
}
__device__ __forceinline__ void add_rel(uint32_t* c) { asm volatile("red.release.gpu.global.add.u32 [%0], 1;" :: "l"(c) : "memory"); }
__device__ __forceinline__ uint32_t tag16(uint32_t ep) { return (ep & 0x7fffu) | 0x8000u; }
__device__ __forceinline__ void gather128(const uint32_t* src, uint32_t tag, unsigned char* dst, int lane, uint32_t sleep) {
    uint4 v;
#pragma unroll 1
    for (uint32_t it = 0; it < SPIN_LIMIT; it++) {
        v = ld_rlx4(src + lane * 4);
        const bool ok = ((((v.x ^ tag) | (v.y ^ tag)) | ((v.z ^ tag) | (v.w ^ tag))) & 0xffffu) == 0;
        if (__all_sync(0xffffffffu, ok)) break;
        __nanosleep(sleep);
    }
    *reinterpret_cast<uint2*>(dst + lane * 8) = make_uint2(prmt(v.x, v.y, 0x7632), prmt(v.z, v.w, 0x7632));
}

__device__ __forceinline__ void bulk_load_nh(uint32_t dst, const void* src, uint32_t bytes, uint32_t bar) {
    asm volatile("cp.async.bulk.shared::cluster.global.mbarrier::complete_tx::bytes [%0], [%1], %2, [%3];"
                 :: "r"(dst), "l"(src), "r"(bytes), "r"(bar) : "memory");
}
__device__ __forceinline__ void tma2d_hint(uint32_t dst, const CUtensorMap* tm, int c0, int c1, uint32_t bar, uint64_t pol) {
    asm volatile("cp.async.bulk.tensor.2d.shared::cluster.global.mbarrier::complete_tx::bytes.L2::cache_hint [%0], [%1, {%3, %4}], [%2], %5;"
                 :: "r"(dst), "l"(tm), "r"(bar), "r"(c0), "r"(c1), "l"(pol) : "memory");
}
__device__ __forceinline__ void tma3d_hint(uint32_t dst, const CUtensorMap* tm, int c0, int c1, int c2, uint32_t bar, uint64_t pol) {
    asm volatile("cp.async.bulk.tensor.3d.shared::cluster.global.mbarrier::complete_tx::bytes.L2::cache_hint [%0], [%1, {%3, %4, %5}], [%2], %6;"
                 :: "r"(dst), "l"(tm), "r"(bar), "r"(c0), "r"(c1), "r"(c2), "l"(pol) : "memory");
}
__device__ __forceinline__ void prefetch32(const void* p) { asm volatile("cp.async.bulk.prefetch.L2.global [%0], 32;" :: "l"(p) : "memory"); }
__device__ __forceinline__ void prefetch_tm(const CUtensorMap* tm) { asm volatile("prefetch.tensormap [%0];" :: "l"(tm) : "memory"); }
__device__ __forceinline__ int kperm(int d) { return (d & ~15) | ((d & 6) << 1) | ((d >> 2) & 2) | (d & 1); }

template <int NK>
__device__ __forceinline__ uint32_t load_wT(uint32_t (&w)[NK][4][4], uint32_t base, int lane) {
    const int r8 = lane & 7;
    const uint32_t a0 = base + (r8 + 8 * (lane >> 4)) * 128 + ((((lane >> 3) & 1) ^ r8) << 4);
    uint32_t dep = 0;
#pragma unroll
    for (int s = 0; s < NK; s++)
#pragma unroll
        for (int mt = 0; mt < 4; mt++) { ldsm4t(w[s][mt], (a0 ^ (mt << 5)) + s * 2048); dep |= w[s][mt][0]; }
    return dep;
}

__device__ __forceinline__ bool mbar_test(uint32_t bar, uint32_t parity) {
    uint32_t done;
    asm volatile("{\n.reg .pred p;\nmbarrier.test_wait.parity.shared::cta.b64 p, [%1], %2;\nselp.u32 %0, 1, 0, p;\n}"
                 : "=r"(done) : "r"(bar), "r"(parity) : "memory");
    return done;
}
__device__ __forceinline__ void st_rlx2x64(void* p, uint32_t a, uint32_t b, uint32_t c, uint32_t d) {
    asm volatile("{\n.reg .b64 u, v;\nmov.b64 u, {%1,%2};\nmov.b64 v, {%3,%4};\nst.relaxed.gpu.global.v2.b64 [%0], {u, v};\n}"
                 :: "l"(p), "r"(a), "r"(b), "r"(c), "r"(d) : "memory");
}
__device__ __forceinline__ void ld_rlx2x64_if(uint4& v, const void* p, uint32_t pred) {
    asm volatile("{\n.reg .pred p;\n.reg .b64 u, v;\nsetp.ne.u32 p, %5, 0;\nmov.b64 u, {%0,%1};\nmov.b64 v, {%2,%3};\n"
                 "@p ld.relaxed.gpu.global.v2.b64 {u, v}, [%4];\nmov.b64 {%0,%1}, u;\nmov.b64 {%2,%3}, v;\n}"
                 : "+r"(v.x), "+r"(v.y), "+r"(v.z), "+r"(v.w) : "l"(p), "r"(pred) : "memory");
}
__device__ __forceinline__ uint4 lds128(uint32_t a) {
    uint4 v; asm volatile("ld.shared.v4.u32 {%0,%1,%2,%3}, [%4];" : "=r"(v.x), "=r"(v.y), "=r"(v.z), "=r"(v.w) : "r"(a) : "memory"); return v;
}
__device__ __forceinline__ float lds32(uint32_t a) { float v; asm volatile("ld.shared.f32 %0, [%1];" : "=f"(v) : "r"(a) : "memory"); return v; }
__device__ __forceinline__ uint32_t untagged(const uint4& v, uint32_t par) {
    uint32_t bad;
    asm("lop3.b32 %0, %1, %2, %3, 0x7e;" : "=r"(bad) : "r"(v.x), "r"(v.z), "r"(par));
    return bad;
}
__device__ __forceinline__ uint32_t or3(uint32_t a, uint32_t b, uint32_t c) {
    uint32_t r; asm("lop3.b32 %0, %1, %2, %3, 0xfe;" : "=r"(r) : "r"(a), "r"(b), "r"(c)); return r;
}
__device__ __forceinline__ void red_bf2(void* p, uint32_t v) {
    asm volatile("red.relaxed.gpu.global.add.noftz.bf16x2 [%0], %1;" :: "l"(p), "r"(v) : "memory");
}

__global__ void __launch_bounds__(NTHREADS, 1) fused_decode_kernel(const __grid_constant__ Hot H, const __grid_constant__ Params P) {
    asm volatile("{\n.reg .pred p;\nsetp.eq.u32 p, %2, 0;\n@p cp.async.bulk.prefetch.L2.global [%0], %1;\n}"
                 :: "l"(H.vp + (size_t)blockIdx.x * CH_BYTES), "n"(PFV), "r"(threadIdx.x) : "memory");
    if (H.never) return;
    const uint64_t pol = policy_evict_first();
    extern __shared__ __align__(1024) unsigned char smem[];
    const uint32_t sb = (uint32_t)__cvta_generic_to_shared(smem);
    const int bid = blockIdx.x, h = bid >> 2, j = bid & 3;
    const int lane = threadIdx.x & 31;
    const int g = lane >> 2, t = lane & 3;
    const uint32_t bar_full = sb + OFF_BAR, bar_empty = bar_full + RING * 8;
    const uint32_t bar_xfull = bar_empty + RING * 8, bar_xempty = bar_xfull + 32, bar_vec = bar_xempty + 32, bar_trig = bar_vec + 16;
    const uint32_t bar_wo = bar_trig + 24, bar_cmb = bar_wo + 32, bar_ini = bar_cmb + 24, bar_gat = bar_ini + 8, bar_qreq = bar_gat + 64, bar_qfull = bar_qreq + 32;
    const uint32_t bar_mempty = bar_qfull + 32, bar_mfull = bar_mempty + 16;
    const uint32_t bar_sfull = bar_mfull + 16, bar_xdone = bar_sfull + 16;
    const int mat = bid & 1, cb = bid >> 1;
    const int ab = h & 3, asplit = h >> 2;
    const int br = j < 2, hp = h & 7, cbk = 2 * (h >> 3) + (j & 1);
    const int hl = br ? 24 + hp : 0;

    const char* kp = H.kp;
    const char* vp = H.vp;
    if (threadIdx.x == 0) {
        mbar_init(bar_full, 1);
        asm volatile("fence.mbarrier_init.release.cluster;" ::: "memory");
        mbar_expect_tx(bar_full, CH_BYTES);
        bulk_load(sb + OFF_RING, kp + bid * CH_BYTES, CH_BYTES, bar_full, pol);
        TL(0); TLG(0);
#pragma unroll
        for (int i = 0; i < 4; i++) mbar_init(bar_xfull + i * 8, 1);
        mbar_init(bar_full + 8, 1);
        mbar_init(bar_ini, 1);
        asm volatile("fence.mbarrier_init.release.cluster;" ::: "memory");
#pragma unroll
        for (int i = 0; i < 4; i++) {
            mbar_expect_tx(bar_xfull + i * 8, CH_BYTES);
            tma2d_hint(sb + OFF_XR + i * CH_BYTES, &P.tm_wq[mat], 64 * cb, 128 * i, bar_xfull + i * 8, pol);
            if (i == 0) {
                mbar_expect_tx(bar_full + 8, CH_BYTES);
                bulk_load(sb + OFF_RING + CH_BYTES, vp + bid * CH_BYTES, CH_BYTES, bar_full + 8, pol);
                mbar_expect_tx(bar_ini, 4096 + 16);
                bulk_load_nh(sb + OFF_EP, &H.S->epoch[4 * h], 16, bar_ini);
                bulk_load_nh(sb + OFF_X, H.x[mat], 4096, bar_ini);
            }
        }
        *reinterpret_cast<int*>(smem + OFF_META) = bid;
#pragma unroll
        for (int i = 2; i < NBAR; i++)
            if ((i < 2 * RING || i >= 2 * RING + 4) && i != I_INI)
                mbar_init(bar_full + i * 8, ((i >= RING && i < 2 * RING) || (i >= NBAR - 5 && i < NBAR - 1)) ? 4
                                          : (i >= 2 * RING + 4 && i < 2 * RING + 10) ? 8 : i == NBAR - 1 ? 9 : 1);
        asm volatile("fence.mbarrier_init.release.cluster;" ::: "memory");
        mbar_arrive(bar_qreq);
    }

    __syncwarp();
    const int warp = __shfl_sync(0xffffffffu, threadIdx.x >> 5, 0);
    auto epoch = [&]() -> uint32_t {
        mbar_wait(bar_ini, 0);
        return __shfl_sync(0xffffffffu, reinterpret_cast<const uint32_t*>(smem + OFF_EP)[j], 0) + 1;
    };

    if (warp >= 12) {
        asm volatile("setmaxnreg.dec.sync.aligned.u32 40;");
        bar_sync(1, 512);
        const uint32_t ep = epoch();
        if (warp == 12) {
            if (lane == 0) {
                uint32_t* tick = &H.S->ticket[ep & 1][threadIdx.x & H.zero];
                if (bid == 0) H.S->ticket[(ep & 1) ^ 1][0] = 0;
                int ntrig = 0, piece = bid, i = 2;
                uint32_t next = 0, tclaim = clock(), tg = 0;
#pragma unroll 1
                for (;; i++) {
                    const int s = i % RING;
                    if (i <= 4) mbar_wait<2048>(bar_xfull + (i - 2) * 8, 0);
                    if (i >= WIN) {
                        mbar_wait(bar_full + ((i - WIN) % RING) * 8, ((i - WIN) / RING) & 1);
                        if (i - WIN < 192) TL2(i - WIN);
                    }
                    if (i >= RING && !mbar_wait(bar_empty + s * 8, ((i / RING) - 1) & 1)) break;
                    if (!(i & 1)) {
                        piece = i == 2 ? NCTA + bid : 2 * NCTA + (int)next;
                        reinterpret_cast<volatile int*>(smem + OFF_META)[s >> 1] = piece < NPIECE ? piece : -1;
                        mbar_arrive(bar_qreq + (s >> 1) * 8);
                        while (ntrig < 3 && piece >= (ntrig == 0 ? TRIG0 : ntrig == 1 ? TRIG1 : TRIG2)) mbar_arrive(bar_trig + 8 * ntrig++);
                        if (piece >= NPIECE) break;
                        tg = tclaim + (NPIECE - piece) * DLR;
                    }
                    mbar_expect_tx(bar_full + s * 8, CH_BYTES);
                    bulk_load(sb + OFF_RING + s * CH_BYTES, ((i & 1) ? vp : kp) + (size_t)piece * CH_BYTES, CH_BYTES, bar_full + s * 8, pol);
                    if ((piece & 127) == 0 && piece + 2 * NCTA < NPIECE) prefetch32(((i & 1) ? vp : kp) + (size_t)(piece + 2 * NCTA) * CH_BYTES);
                    if ((piece >> 7) == 60) prefetch32(P.wo[br] + (hp + 16 * (i & 1)) * 65536 + 64 * cbk);
                    if (i & 1) {
                        if (hl >= HS && piece >= NPIECE - XS) next = NPIECE - 2 * NCTA;
                        else { next = take_ticket(tick); tclaim = clock(); }
                    }
                }
                mbar_wait(bar_xdone, 0);
                if (i >= RING) mbar_wait(bar_empty + (i % RING) * 8 + 8, ((i / RING) - 1) & 1);
                const int tlook = TG - (31 - hl) * 64 * DLR;
                bool look = hl >= HS;
                auto since = [&]() -> int {
                    const int now = (int)((uint32_t)clock() - tg);
                    if (look && now >= tlook) { mbar_arrive(bar_cmb + 16); look = false; }
                    return now;
                };
#pragma unroll 1
                for (int k = 0; k < 4; k++) {
                    const uint32_t dst = sb + (k < 2 ? OFF_RING + (i % RING) * CH_BYTES : OFF_XR) + k * CH_BYTES;
                    const int wi = k - 2;
                    const uint32_t wb = wi >= 0 ? bar_wo + wi * 8 : bar_full + ((i + wi) % RING) * 8, wp = wi >= 0 ? 0 : ((i + wi) / RING) & 1;
                    while (wi >= 0 && hl < HS && since() < NB2 + wi * NBS) {}
                    while (!mbar_test(wb, wp) && since() < DL0 + k * DLS) {}
                    mbar_expect_tx(bar_wo + k * 8, CH_BYTES);
                    tma2d_hint(dst, &P.tm_wo[br], 64 * cbk, (hp + 8 * k) * 128, bar_wo + k * 8, pol);
                }
                while (look) since();
                TL(1);
            }
        } else if (warp == 15) {
            const uint32_t par = ep & 1;
            const uint32_t t0 = 64 * (32 * j + h + 1) + LAG, t1 = 64 * (96 + (hl < HURG ? hl : hl - 8) + 1) + LAG + LAG1, t2 = 64 * (96 + hl + 1) + LAG2;
            uint32_t fired = 0;
#pragma unroll 1
            for (int r = 0;; r++) {
                const unsigned char* mg = smem + OFF_MG + (r & 1) * MG_BYTES;
                if (!mbar_wait(bar_sfull + (r & 1) * 8, (r >> 1) & 1)) break;
                const uint32_t piece = *reinterpret_cast<const uint32_t*>(mg + 2048 + 144);
                if (piece < NPIECE) {
                    const float4 mw = *reinterpret_cast<const float4*>(mg + 2048 + 128);
                    const float mm = fmaxf(fmaxf(mw.x, mw.y), fmaxf(mw.z, mw.w));
                    const float e0 = ex2((mw.x - mm) * LOG2E), e1 = ex2((mw.y - mm) * LOG2E);
                    const float e2 = ex2((mw.z - mm) * LOG2E), e3 = ex2((mw.w - mm) * LOG2E);
                    float l = reinterpret_cast<const float*>(mg + 2048)[lane] * ((lane & 16) ? ((lane & 8) ? e3 : e2) : ((lane & 8) ? e1 : e0));
#pragma unroll
                    for (int o = 16; o > 0; o >>= 1) l += __shfl_xor_sync(0xffffffffu, l, o);
                    uint32_t* dst = &H.S->pB[piece][lane * 4];
                    if (piece >= NPIECE - 512) mbar_wait(bar_xdone, 0);
                    if (lane < 2) st_rlx2x64(&H.S->mlB[piece][lane * 4], tagf(l, par), __float_as_uint(mm), par, 0);
                    mbar_wait(bar_mfull + (r & 1) * 8, (r >> 1) & 1);
                    const float4 a = reinterpret_cast<const float4*>(mg)[lane],      b = reinterpret_cast<const float4*>(mg)[32 + lane];
                    const float4 c = reinterpret_cast<const float4*>(mg)[64 + lane], d = reinterpret_cast<const float4*>(mg)[96 + lane];
                    st_rlx2x64(dst, tagf((a.x * e0 + b.x * e1) + (c.x * e2 + d.x * e3), par), __float_as_uint((a.y * e0 + b.y * e1) + (c.y * e2 + d.y * e3)),
                                    tagf((a.z * e0 + b.z * e1) + (c.z * e2 + d.z * e3), par), __float_as_uint((a.w * e0 + b.w * e1) + (c.w * e2 + d.w * e3)));
                    TL3(3, 0);
                }
                __syncwarp();
                const uint32_t now = (piece >= t0 ? 1u : 0u) | (piece >= t1 ? 2u : 0u) | (piece >= t2 && hl < HS ? 4u : 0u);
                if (lane < 3 && ((now & ~fired) >> lane & 1)) mbar_arrive(bar_cmb + lane * 8);
                fired = now;
                if (piece >= NPIECE) break;
                if (lane == 0) mbar_arrive(bar_mempty + (r & 1) * 8);
            }
        } else if (warp == 14) {
            mbar_wait<2048>(bar_xfull + 24, 0);
            __nanosleep(QD0);
#pragma unroll 1
            for (int r = 0;; r++) {
                if (!mbar_wait(bar_qreq + (r & 3) * 8, (r >> 2) & 1)) break;
                const int piece = reinterpret_cast<volatile int*>(smem + OFF_META)[r & 3];
                if (piece >= 0) gather128(&H.S->q[0][piece >> 11][((piece >> 6) & 31) * 128], tag16(ep), smem + OFF_QT + (r & 3) * 256, lane, QD1);
                __syncwarp();
                if (lane == 0) mbar_arrive(bar_qfull + (r & 3) * 8);
                if (piece < 0) break;
            }
        } else if (warp == 13) {
            if (lane == 0) { prefetch_tm(&P.tm_wuk); prefetch_tm(j == 0 ? &P.tm_ckv : &P.tm_wuv); }
            int n = 4;
            auto acquire = [&](uint32_t bytes) -> uint32_t {
                mbar_wait(bar_xempty + (n & 3) * 8, ((n >> 2) - 1) & 1);
                mbar_expect_tx(bar_xfull + (n & 3) * 8, bytes);
                return (uint32_t)(n++ & 3);
            };
            if (lane == 0) {
#pragma unroll 1
                for (int k = 0; k < 2; k++) {
                    const uint32_t s = acquire(CH_BYTES);
                    tma2d_hint(sb + OFF_XR + s * CH_BYTES, &P.tm_wuk, h * 128 + 64 * k, 128 * j, bar_xfull + s * 8, pol);
                }
                if (j >= 2) {
                    mbar_wait(bar_trig, 0);
#pragma unroll 1
                    for (int k = 0; k < 4; k++) {
                        const uint32_t s = acquire(CH_BYTES);
                        tma2d_hint(sb + OFF_XR + s * CH_BYTES, &P.tm_wuv, h * 128 + 64 * (j - 2), 128 * k, bar_xfull + s * 8, pol);
                    }
                }
            }
            __syncwarp();
            if (j == 0) bar_sync(10, 64);
            if (lane == 0) {
                if (j == 0) wait_count(H.S->cntQ, ep * NCTA, QSLEEP);
                else if (j >= 2) { mbar_wait(bar_trig + 8, 0); wait_count(H.S->cntA, ep * 4 * A_SPLITS, FSLEEP); }
                asm volatile("fence.proxy.async.global;" ::: "memory");
                if (j == 0) {
#pragma unroll 1
                    for (int k = 0; k < 4; k++) {
                        const uint32_t s = acquire(CH_BYTES);
                        bulk_load_nh(sb + OFF_XR + s * CH_BYTES, &H.S->qabs[ab][2 * k][0][0][0][0][0], CH_BYTES, bar_xfull + s * 8);
                    }
#pragma unroll 1
                    for (int k = 0; k < A_TILES; k++) {
                        const uint32_t s = acquire(CH_BYTES);
                        tma3d_hint(sb + OFF_XR + s * CH_BYTES, &P.tm_ckv, 0, ab * 4096 + 16 * (k * A_SPLITS + asplit), 0, bar_xfull + s * 8, pol);
                    }
                } else if (j >= 2) {
#pragma unroll 1
                    for (int k = 0; k < 4; k++) {
                        const uint32_t s = acquire(CH_BYTES + A_SPLITS * 8);
                        bulk_load_nh(sb + OFF_XR + s * CH_BYTES, &H.S->pA[h][k][0][0], CH_BYTES, bar_xfull + s * 8);
                        bulk_load_nh(sb + OFF_MLA + k * A_SPLITS * 8, &H.S->mlA[h][k][0], A_SPLITS * 8, bar_xfull + s * 8);
                    }
                }
            }
            __syncwarp();
            mbar_wait(bar_trig + 16, 0);
            if (lane == 0) {
                prefetch_tm(&P.tm_wo[br]);
                wait_count(H.S->cntQ, ep * NCTA, QSLEEP);
                mbar_arrive(bar_xdone);
            }
        }
    } else if (warp < 4) {
        asm volatile("setmaxnreg.dec.sync.aligned.u32 88;");
        bar_sync(1, 512);
        const uint32_t ep = epoch();
        const bool valid = (t == (g >> 1));
        const bool odd = g & 1;
        const int r8 = lane & 7;
        const uint32_t koff = (warp * 16 + r8 + 8 * ((lane >> 3) & 1)) * 256 + (((lane >> 4) ^ r8) << 4);
        const uint32_t voff = (warp * 16 + r8 + 8 * (lane >> 4)) * 256 + ((((lane >> 3) & 1) ^ r8) << 4);
        int r = 0;
#pragma unroll 1
        for (;; r++) {
            const int sk = (2 * r) % RING, sv = sk + 1;
            const uint32_t ph = ((2 * r) / RING) & 1;
            unsigned char* mg = smem + OFF_MG + (r & 1) * MG_BYTES;
            if (!mbar_wait(bar_qfull + (r & 3) * 8, ph)) break;
            if (r == 0 && threadIdx.x == 0) TL(4);
            const int piece = reinterpret_cast<volatile int*>(smem + OFF_META)[r & 3];
            if (piece < 0) {
                mbar_wait(bar_mempty + (r & 1) * 8, ((r >> 1) - 1) & 1);
                if (lane == 0) { *reinterpret_cast<int*>(mg + 2048 + 144) = piece; mbar_arrive(bar_sfull + (r & 1) * 8); }
                break;
            }
            uint32_t qf[16];
#pragma unroll
            for (int u = 0; u < 16; u++) qf[u] = reinterpret_cast<const uint32_t*>(smem + OFF_QT + (r & 3) * 256)[4 * (u ^ g) + t];
            mbar_wait(bar_full + sk * 8, ph);
            const uint32_t ka = sb + OFF_RING + sk * CH_BYTES + koff;
            float c0[4] = {0.f, 0.f, 0.f, 0.f}, c1[4] = {0.f, 0.f, 0.f, 0.f};
#pragma unroll
            for (int s = 0; s < 8; s += 2) {
                uint32_t a[4], b[4];
                ldsm4(a, ka ^ (s << 5));
                ldsm4(b, ka ^ ((s + 1) << 5));
                mma(c0, a[0], a[1], a[2], a[3], qf[2 * s], qf[2 * s + 1]);
                mma(c1, b[0], b[1], b[2], b[3], qf[2 * s + 2], qf[2 * s + 3]);
            }
            float slo = odd ? c0[1] + c1[1] : c0[0] + c1[0];
            float shi = odd ? c0[3] + c1[3] : c0[2] + c1[2];
            if (lane == 0) mbar_arrive(bar_empty + sk * 8 + (__float_as_uint(slo) & H.zero));
            slo = bf16_round(bf16_round(slo) * SCALE);
            shi = bf16_round(bf16_round(shi) * SCALE);
            const float m = warp_max(valid ? fmaxf(slo, shi) : -INFINITY);
            const float plo = valid ? ex2((slo - m) * LOG2E) : 0.f;
            const float phi = valid ? ex2((shi - m) * LOG2E) : 0.f;
            if (r >= 2) mbar_wait(bar_mempty + (r & 1) * 8, ((r >> 1) - 1) & 1);
            if (valid) reinterpret_cast<float*>(mg + 2048)[warp * 8 + g] = plo + phi;
            if (lane == 0) { reinterpret_cast<float*>(mg + 2048 + 128)[warp] = m; *reinterpret_cast<int*>(mg + 2048 + 144) = piece; }
            __syncwarp();
            if (lane == 0) mbar_arrive(bar_sfull + (r & 1) * 8);
            const uint32_t b0 = odd ? pack_bf16(0.f, plo) : pack_bf16(plo, 0.f);
            const uint32_t b1 = odd ? pack_bf16(0.f, phi) : pack_bf16(phi, 0.f);
            mbar_wait(bar_full + sv * 8, ph);
            if (warp == 0) TL3(0, 0);
            const uint32_t va = sb + OFF_RING + sv * CH_BYTES + voff;
            float ev[8], od[8];
#pragma unroll
            for (int i = 0; i < 8; i++) {
                uint32_t a[4];
                float acc[4] = {0.f, 0.f, 0.f, 0.f};
                ldsm4t(a, va ^ (i << 5));
                mma(acc, a[0], a[1], a[2], a[3], b0, b1);
                ev[i] = acc[0] + acc[3]; od[i] = acc[1] + acc[2];
            }
#pragma unroll
            for (int i = 0; i < 8; i += 2) {
                ev[i] += __shfl_xor_sync(0xffffffffu, ev[i + 1], 1);
                od[i] += __shfl_xor_sync(0xffffffffu, od[i + 1], 1);
            }
#pragma unroll
            for (int i = 0; i < 8; i += 4) {
                ev[i] += __shfl_xor_sync(0xffffffffu, ev[i + 2], 2);
                od[i] += __shfl_xor_sync(0xffffffffu, od[i + 2], 2);
            }
            reinterpret_cast<float4*>(mg)[warp * 32 + lane] = make_float4(ev[0], od[0], ev[4], od[4]);
            __syncwarp();
            if (lane == 0) {
                mbar_arrive(bar_mfull + (r & 1) * 8);
                mbar_arrive(bar_empty + sv * 8 + ((__float_as_uint(ev[0]) | __float_as_uint(ev[4])) & H.zero));
            }
        }
        TL3(2, 0);
        {
            int lane2 = lane;
            asm volatile("" : "+r"(lane2));
            const int g2 = lane2 >> 2;
            uint16_t* outp = reinterpret_cast<uint16_t*>(P.out) + (lane2 & 3) * 1024 + 512 * br + 64 * cbk + 16 * warp + ((g2 & 1) ? g2 + 7 : g2);
            const uint32_t sel = (g2 & 1) ? 0x3276 : 0x5410;
            const uint32_t aoff = (r8 + 8 * (lane2 >> 4)) * 128 + (((2 * warp + ((lane2 >> 3) & 1)) ^ r8) << 4);
            uint32_t a0 = sb + OFF_RING + ((2 * r) % RING) * CH_BYTES + aoff;
            uint32_t vp0 = sb + OFF_SS + (g2 >> 1) * 288 + 8 * (lane2 & 3);
            float d[4][4];
#pragma unroll
            for (int u = 0; u < 4; u++) d[u][0] = d[u][1] = d[u][2] = d[u][3] = 0.f;
            uint2 ob[8];
            auto load_v = [&]() {
#pragma unroll
                for (int s = 0; s < 8; s++)
                    asm volatile("ld.shared.v2.u32 {%0,%1}, [%2];" : "=r"(ob[s].x), "=r"(ob[s].y) : "r"(vp0 + 32 * s) : "memory");
            };
            bool have = false;
#pragma unroll 1
            for (int k = 0;; k++) {
                uint32_t wf[8][4];
                mbar_wait(bar_wo + k * 8, 0);
#pragma unroll
                for (int s = 0; s < 8; s++) ldsm4t(wf[s], a0 + s * 2048);
                if (!have) { mbar_wait(bar_vec + (k ? 8 : 0), 0); load_v(); }
                have = mbar_test(bar_vec + (k == 2 ? 8 : 0), 0);
#pragma unroll
                for (int s = 0; s < 8; s++) mma(d[s & 3], wf[s][0], wf[s][1], wf[s][2], wf[s][3], ob[s].x, ob[s].y);
                if (k == 3) break;
                a0 = k == 1 ? sb + OFF_XR + 2 * CH_BYTES + aoff : a0 + CH_BYTES;
                vp0 += 4 * 288;
                if (have) load_v();
            }
            const uint32_t e = pack_bf16((d[0][0] + d[1][0]) + (d[2][0] + d[3][0]), (d[0][2] + d[1][2]) + (d[2][2] + d[3][2]));
            red_bf2(outp, prmt(e, __shfl_xor_sync(0xffffffffu, e, 4), sel));
            TL3(12, 0);
        }
    } else {
        asm volatile("setmaxnreg.inc.sync.aligned.u32 192;");
        const int x = warp - 4, tid = threadIdx.x - 128;
        bar_sync(1, 512);
        const uint32_t ep = epoch();
        const uint32_t tag = tag16(ep), par = ep & 1;
        uint32_t* qdst = &H.S->q[mat][tid >> 6][mat ? kperm(64 * cb + (tid & 63)) : 64 * cb + (tid & 63)];
        st_rlx(qdst, 0);
        if (j >= 2) st_rlx(&H.S->vec[0][h][tid >> 6][kperm(64 * (j - 2) + (tid & 63))], 0);
        if (tid < 128) st_rlx(&H.S->vec[1][h][j][tid], 0);
        if (tid < 16) reinterpret_cast<uint32_t*>(P.out)[bid * 16 + tid] = 0u;
        if (!mat) {
            st_rlx4(&H.S->pB[NPIECE - 512 + 8 * cb + x][lane * 4], par ^ 1, par ^ 1, par ^ 1, par ^ 1);
            if (lane < 2) st_rlx4(&H.S->mlB[NPIECE - 512 + 8 * cb + x][lane * 4], par ^ 1, par ^ 1, par ^ 1, par ^ 1);
        }
        const uint32_t xr = sb + OFF_XR;
        auto xwait = [&](int n) { mbar_wait(bar_xfull + (n & 3) * 8, (n >> 2) & 1); };
        auto xrel  = [&](int n, uint32_t dep) { if (lane == 0) mbar_arrive(bar_xempty + (n & 3) * 8 + (dep & H.zero)); };
        float* red = reinterpret_cast<float*>(smem + OFF_SS + 8448);
        {
            uint32_t w[4][4][4], xb[4][2];
#pragma unroll
            for (int s = 0; s < 4; s++) {
                const uint32_t* X = reinterpret_cast<const uint32_t*>(smem + OFF_X) + (g & 3) * 256 + 32 * x + 8 * s + t;
                xb[s][0] = X[0]; xb[s][1] = X[4];
            }
            xwait(x >> 1);
            const uint32_t dep = load_wT<4>(w, xr + x * 8192, lane);
            float acc[4][4];
#pragma unroll
            for (int u = 0; u < 4; u++) acc[u][0] = acc[u][1] = acc[u][2] = acc[u][3] = 0.f;
#pragma unroll
            for (int s = 0; s < 4; s++)
#pragma unroll
                for (int mt = 0; mt < 4; mt++) mma(acc[mt], w[s][mt][0], w[s][mt][1], w[s][mt][2], w[s][mt][3], xb[s][0], xb[s][1]);
#pragma unroll
            for (int n = 0; n < 4; n++) xrel(n, dep);
            if (t < 2) {
#pragma unroll
                for (int mt = 0; mt < 4; mt++) {
                    float* r0 = red + (x * 4 + 2 * t) * 64 + 16 * mt + g;
                    r0[0] = acc[mt][0]; r0[8] = acc[mt][2]; r0[64] = acc[mt][1]; r0[72] = acc[mt][3];
                }
            }
            bar_sync(2, 256);
            float s = 0.f;
#pragma unroll
            for (int i = 0; i < 8; i++) s += red[i * 256 + tid];
            st_rlx(qdst, (pack_bf16(0.f, s) & 0xffff0000u) | tag);
        }
        if (tid == 0) TL(6);
        {
            uint32_t w[8][4];
            const int r8 = lane & 7;
            const uint32_t a0 = xr + (16 * x + r8 + 8 * ((lane >> 3) & 1)) * 128 + (((lane >> 4) ^ r8) << 4);
#pragma unroll
            for (int hf = 0; hf < 2; hf++) {
                xwait(4 + hf);
                uint32_t dep = 0;
#pragma unroll
                for (int ks = 0; ks < 4; ks++) { ldsm4(w[4 * hf + ks], (a0 ^ (ks << 5)) + hf * CH_BYTES); dep |= w[4 * hf + ks][0]; }
                xrel(4 + hf, dep);
            }
            if (x < 4) gather128(&H.S->q[1][x][h * 128], tag, smem + OFF_OA + x * 288, lane, QD1);
            bar_sync(2, 256);
            float c[4] = {0.f, 0.f, 0.f, 0.f};
#pragma unroll
            for (int i = 0; i < 8; i++) {
                const uint2 b = *reinterpret_cast<const uint2*>(smem + OFF_OA + (g & 3) * 288 + (16 * i + 4 * t) * 2);
                mma(c, w[i][0], w[i][1], w[i][2], w[i][3], b.x, b.y);
            }
            uint16_t* stg = reinterpret_cast<uint16_t*>(smem + OFF_SS);
            if (t < 2) {
                const int ks = x & 3;
#pragma unroll
                for (int q = 0; q < 4; q++) {
                    const int b = 2 * t + (q & 1), rg = q >> 1;
                    const float vh = bf16_round(c[q]);
                    const int o = b * 256 + (x >> 2) * 128 + (ks >> 1) * 32 + (g >> 1) * 8 + (ks & 1) * 4 + rg * 2 + (g & 1);
                    stg[o]      = (uint16_t)(__float_as_uint(vh) >> 16);
                    stg[o + 64] = (uint16_t)pack_bf16(c[q] - vh, 0.f);
                }
            }
            bar_sync(2, 256);
            if (tid < 128) {
                const uint4 val = reinterpret_cast<const uint4*>(stg)[tid];
                *reinterpret_cast<uint4*>(&H.S->qabs[tid >> 5][2 * j + ((tid >> 4) & 1)][(tid >> 3) & 1][h >> 3][(tid >> 2) & 1][(h & 7) * 4 + (tid & 3)][0]) = val;
            }
            bar_sync(2, 256);
            if (tid == 0) { add_rel(H.S->cntQ); TL(7); }
            if (j == 0 && x == 0) bar_arrive(10, 64);
        }
        if (j == 0) {
            uint32_t qf[2][4][8];
#pragma unroll
            for (int k = 0; k < 4; k++) {
                xwait(6 + k);
                uint32_t dep = 0;
                if (k == (x >> 1)) {
                    const unsigned char* qp = smem + OFF_XR + ((6 + k) & 3) * CH_BYTES + (x & 1) * 8192 + lane * 16;
#pragma unroll
                    for (int i = 0; i < 16; i++) {
                        const uint4 a = *reinterpret_cast<const uint4*>(qp + i * 512);
                        uint32_t* d = &qf[i >> 3][(i >> 1) & 3][4 * (i & 1)];
                        d[0] = a.x; d[1] = a.y; d[2] = a.z; d[3] = a.w;
                        dep |= a.x;
                    }
                }
                xrel(6 + k, dep);
            }
            if (tid == 0) TL(8);
            float acc[4][4][4];
#pragma unroll
            for (int a = 0; a < 4; a++)
#pragma unroll
                for (int b = 0; b < 4; b++) acc[a][b][0] = acc[a][b][1] = acc[a][b][2] = acc[a][b][3] = 0.f;
            float m = -INFINITY, l = 0.f;
            const int r8 = lane & 7;
            const uint32_t koff = x * 2048 + (r8 + 8 * ((lane >> 3) & 1)) * 128 + (((lane >> 4) ^ r8) << 4);
            const uint32_t voff = x * 2048 + (r8 + 8 * (lane >> 4)) * 128 + ((((lane >> 3) & 1) ^ r8) << 4);
            const int sh = tid >> 3, skp = tid & 7;
#define CK0
#define CK1(v)
            for (int n = 10; n < 10 + A_TILES; n++) {
                CK0
                xwait(n);
                CK1(cw)
                const uint32_t base = xr + (n & 3) * CH_BYTES;
                float S[4][4];
#pragma unroll
                for (int nt = 0; nt < 4; nt++) S[nt][0] = S[nt][1] = S[nt][2] = S[nt][3] = 0.f;
#pragma unroll
                for (int ks = 0; ks < 4; ks++) {
                    uint32_t a[4];
                    ldsm4(a, base + (koff ^ (ks << 5)));
#pragma unroll
                    for (int nt = 0; nt < 4; nt++) mma(S[nt], a[0], a[1], a[2], a[3], qf[1][nt][2 * ks], qf[1][nt][2 * ks + 1]);
#pragma unroll
                    for (int nt = 0; nt < 4; nt++) mma(S[nt], a[0], a[1], a[2], a[3], qf[0][nt][2 * ks], qf[0][nt][2 * ks + 1]);
                }
#pragma unroll
                for (int nt = 0; nt < 4; nt++) {
                    unsigned char* sp = smem + OFF_SS + (x * 32 + 8 * nt + 2 * t) * 80 + 8 * g;
                    *reinterpret_cast<float2*>(sp) = make_float2(S[nt][0], S[nt][2]);
                    *reinterpret_cast<float2*>(sp + 80) = make_float2(S[nt][1], S[nt][3]);
                }
                bar_sync(2, 256);
                CK1(c1)
                float s0 = 0.f, s1 = 0.f;
#pragma unroll
                for (int w = 0; w < 8; w++) {
                    const float2 v = *reinterpret_cast<const float2*>(smem + OFF_SS + (w * 32 + sh) * 80 + 8 * skp);
                    s0 += v.x; s1 += v.y;
                }
                s0 = bf16_round(bf16_round(s0) * SCALE);
                s1 = bf16_round(bf16_round(s1) * SCALE);
                float mx = fmaxf(s0, s1);
                mx = fmaxf(mx, __shfl_xor_sync(0xffffffffu, mx, 1));
                mx = fmaxf(mx, __shfl_xor_sync(0xffffffffu, mx, 2));
                mx = fmaxf(mx, __shfl_xor_sync(0xffffffffu, mx, 4));
                mx = fmaxf(mx, m);
                const float al = ex2((m - mx) * LOG2E);
                m = mx;
                const float p0 = ex2((s0 - m) * LOG2E), p1 = ex2((s1 - m) * LOG2E);
                l = l * al + p0 + p1;
                {
                    const uint32_t pp = pack_bf16(p0, p1);
                    uint16_t* dst = reinterpret_cast<uint16_t*>(smem + OFF_SP) + sh * 16 + kperm(skp);
                    dst[0] = (uint16_t)pp; dst[2] = (uint16_t)(pp >> 16);
                }
                if (skp == 0) reinterpret_cast<float*>(smem + OFF_ALPHA)[sh] = al;
                bar_sync(2, 256);
                CK1(c2)
                uint2 pb[4];
#pragma unroll
                for (int nt = 0; nt < 4; nt++) {
                    pb[nt] = *reinterpret_cast<const uint2*>(smem + OFF_SP + (8 * nt + g) * 32 + 8 * t);
                    const float2 a2 = *reinterpret_cast<const float2*>(smem + OFF_ALPHA + (8 * nt + 2 * t) * 4);
#pragma unroll
                    for (int mt = 0; mt < 4; mt++) {
                        acc[mt][nt][0] *= a2.x; acc[mt][nt][1] *= a2.y; acc[mt][nt][2] *= a2.x; acc[mt][nt][3] *= a2.y;
                    }
                }
                uint32_t dep = 0;
#pragma unroll
                for (int mt = 0; mt < 4; mt++) {
                    uint32_t a[4];
                    ldsm4t(a, base + (voff ^ (mt << 5)));
                    dep |= a[0];
#pragma unroll
                    for (int nt = 0; nt < 4; nt++) mma(acc[mt][nt], a[0], a[1], a[2], a[3], pb[nt].x, pb[nt].y);
                }
                xrel(n, dep);
                CK1(c3)
            }
#pragma unroll
            for (int nt = 0; nt < 4; nt++)
#pragma unroll
                for (int e = 0; e < 2; e++) {
                    float* dst = &H.S->pA[8 * nt + 2 * t + e][ab][asplit][64 * x + 4 * g];
                    *reinterpret_cast<float4*>(dst)      = make_float4(acc[0][nt][e], acc[0][nt][2 + e], acc[1][nt][e], acc[1][nt][2 + e]);
                    *reinterpret_cast<float4*>(dst + 32) = make_float4(acc[2][nt][e], acc[2][nt][2 + e], acc[3][nt][e], acc[3][nt][2 + e]);
                }
            l += __shfl_xor_sync(0xffffffffu, l, 1);
            l += __shfl_xor_sync(0xffffffffu, l, 2);
            l += __shfl_xor_sync(0xffffffffu, l, 4);
            if (skp == 0) H.S->mlA[sh][ab][asplit] = make_float2(m, l);
            bar_sync(2, 256);
            if (tid == 0) { add_rel(H.S->cntA); TL(9); }
        } else if (j >= 2) {
            uint32_t wv[4][4][4];
#pragma unroll
            for (int k = 0; k < 4; k++) {
                xwait(6 + k);
                uint32_t dep = 0;
                if (k == (x >> 1)) dep = load_wT<4>(wv, xr + ((6 + k) & 3) * CH_BYTES + (x & 1) * 8192, lane);
                xrel(6 + k, dep);
            }
            {
                const int b = tid >> 6, xx = (tid >> 3) & 7, gg = tid & 7;
                xwait(10 + b);
                if (tid == 0) TL(8);
                const float2* mlp = reinterpret_cast<const float2*>(smem + OFF_MLA) + b * A_SPLITS;
                float mm = -INFINITY, ll = 0.f;
#pragma unroll
                for (int s = 0; s < A_SPLITS; s++) mm = fmaxf(mm, mlp[s].x);
#pragma unroll
                for (int s = 0; s < A_SPLITS; s++) ll += mlp[s].y * ex2((mlp[s].x - mm) * LOG2E);
                const float inv = 1.f / ll;
                float cl[8];
#pragma unroll
                for (int e = 0; e < 8; e++) cl[e] = 0.f;
                const float* src = reinterpret_cast<const float*>(smem + OFF_XR + ((10 + b) & 3) * CH_BYTES) + 64 * xx + 4 * gg;
#pragma unroll
                for (int s = 0; s < A_SPLITS; s++) {
                    const float wt = ex2((mlp[s].x - mm) * LOG2E) * inv;
                    const float4 a = *reinterpret_cast<const float4*>(src + s * 512), c = *reinterpret_cast<const float4*>(src + s * 512 + 32);
                    cl[0] += wt * a.x; cl[1] += wt * a.y; cl[2] += wt * a.z; cl[3] += wt * a.w;
                    cl[4] += wt * c.x; cl[5] += wt * c.y; cl[6] += wt * c.z; cl[7] += wt * c.w;
                }
                uint16_t* hi = reinterpret_cast<uint16_t*>(smem + OFF_SS + b * 1056);
                uint16_t* lo = reinterpret_cast<uint16_t*>(smem + OFF_SS + (b + 4) * 1056);
#pragma unroll
                for (int e = 0; e < 8; e++) {
                    const int c = kperm(64 * xx + 8 * e + gg);
                    const float vh = bf16_round(cl[e]);
                    hi[c] = (uint16_t)(__float_as_uint(vh) >> 16);
                    lo[c] = (uint16_t)pack_bf16(cl[e] - vh, 0.f);
                }
                bar_sync(2, 256);
#pragma unroll
                for (int k = 0; k < 4; k++) xrel(10 + k, __float_as_uint(cl[0]) | __float_as_uint(cl[4]));
            }
            {
                float acc[4][4];
#pragma unroll
                for (int u = 0; u < 4; u++) acc[u][0] = acc[u][1] = acc[u][2] = acc[u][3] = 0.f;
#pragma unroll
                for (int s = 0; s < 4; s++) {
                    const uint2 b = *reinterpret_cast<const uint2*>(smem + OFF_SS + g * 1056 + (64 * x + 16 * s + 4 * t) * 2);
#pragma unroll
                    for (int mt = 0; mt < 4; mt++) mma(acc[mt], wv[s][mt][0], wv[s][mt][1], wv[s][mt][2], wv[s][mt][3], b.x, b.y);
                }
#pragma unroll
                for (int mt = 0; mt < 4; mt++)
#pragma unroll
                    for (int e = 0; e < 4; e++) acc[mt][e] += __shfl_xor_sync(0xffffffffu, acc[mt][e], 2);
                if (t < 2) {
#pragma unroll
                    for (int mt = 0; mt < 4; mt++) {
                        float* r0 = red + (x * 4 + 2 * t) * 64 + 16 * mt + g;
                        r0[0] = acc[mt][0]; r0[8] = acc[mt][2]; r0[64] = acc[mt][1]; r0[72] = acc[mt][3];
                    }
                }
            }
            bar_sync(2, 256);
            {
                float s = 0.f;
#pragma unroll
                for (int i = 0; i < 8; i++) s += red[i * 256 + tid];
                st_rlx(&H.S->vec[0][h][tid >> 6][kperm(64 * (j - 2) + (tid & 63))], (pack_bf16(0.f, s) & 0xffff0000u) | tag);
            }
            if (tid == 0) TL(9);
        }
        {
            __syncwarp();
            if (lane == 0) mbar_arrive(bar_xdone);
#pragma unroll 1
            for (uint32_t pass = H.zero; pass < 2; pass++) {
                if (pass == br) {
                    mbar_wait(br ? bar_cmb + 8 : bar_trig + 16, 0);
#pragma unroll 1
                    for (int u = 2 * x; u < 2 * x + 2; u++)
                        if (u < 15 || hl < HURG) gather128(&H.S->vec[br][hp + 8 * (u >> 2)][u & 3][0], tag, smem + OFF_SS + u * 288, lane, QD1);
                    __syncwarp();
                    if (lane == 0) { mbar_arrive(bar_vec); if (hl < HURG) mbar_arrive(bar_vec + 8); }
                    TL3(13, 0);
                    if (tid == 0) { H.S->epoch[bid] = ep; TL(10); }
                }
                if (pass ? hl >= HURG : (j < 3 || h < HURG)) {
                    const int pr = pass ? 96 + hl : 32 * j + h;
                    const uint32_t* rp = &H.S->pB[64 * pr + 8 * x][lane * 4];
                    const uint32_t* sp = &H.S->mlB[64 * pr + 8 * x + (lane & 7)][0];
                    uint4 v[8], sv;
                    mbar_wait(bar_cmb + pass * 16, 0);
                    TL3(5, 0);
                    if (lane == 0) {
                        mbar_expect_tx(bar_gat + x * 8, 4096 + 256);
                        bulk_load_nh(xr + x * 4096, rp, 4096, bar_gat + x * 8);
                        bulk_load_nh(sb + OFF_ST + x * 256, sp, 256, bar_gat + x * 8);
                    }
                    __syncwarp();
                    mbar_wait(bar_gat + x * 8, pass);
                    TL3(15, 0);
                    sv = lds128(sb + OFF_ST + x * 256 + (lane & 7) * 32);
#pragma unroll
                    for (int i = 0; i < 8; i++) v[i] = lds128(xr + x * 4096 + i * 512 + lane * 16);
                    float mx, ll, wt[8];
#pragma unroll 1
                    for (uint32_t it = 0;; it++) {
                        uint32_t bad[9];
#pragma unroll
                        for (int i = 0; i < 8; i++) bad[i] = untagged(v[i], par);
                        bad[8] = untagged(sv, par);
                        const uint32_t anyb = or3(or3(bad[0], bad[1], bad[2]), or3(bad[3], bad[4], bad[5]), or3(bad[6], bad[7], bad[8]));
                        const float m0 = __uint_as_float(sv.y);
                        mx = warp_max(m0);
                        const float w0 = ex2((m0 - mx) * LOG2E);
                        ll = w0 * __uint_as_float(sv.x);
                        const float l4 = __shfl_xor_sync(0xffffffffu, ll, 4);
#pragma unroll
                        for (int i = 0; i < 8; i++) wt[i] = __shfl_sync(0xffffffffu, w0, i);
                        ll += l4;
                        ll += __shfl_xor_sync(0xffffffffu, ll, 2);
                        if (!__any_sync(0xffffffffu, anyb & 1) || it >= SPIN_LIMIT) break;
                        uint32_t mask = 0;
#pragma unroll
                        for (int i = 0; i < 9; i++) mask |= (bad[i] & 1) << i;
                        const uint32_t pend = __reduce_or_sync(0xffffffffu, mask);
                        ld_rlx2x64_if(sv, sp, pend & 256);
#pragma unroll
                        for (int i = 0; i < 8; i++) ld_rlx2x64_if(v[i], rp + i * 128, pend & (1 << i));
                    }
                    ll += __shfl_xor_sync(0xffffffffu, ll, 1);
                    float4 acc = make_float4(0.f, 0.f, 0.f, 0.f), acd = acc;
#pragma unroll
                    for (int i = 0; i < 8; i += 2) {
                        acc.x += wt[i] * __uint_as_float(v[i].x); acc.y += wt[i] * __uint_as_float(v[i].y);
                        acc.z += wt[i] * __uint_as_float(v[i].z); acc.w += wt[i] * __uint_as_float(v[i].w);
                        acd.x += wt[i + 1] * __uint_as_float(v[i + 1].x); acd.y += wt[i + 1] * __uint_as_float(v[i + 1].y);
                        acd.z += wt[i + 1] * __uint_as_float(v[i + 1].z); acd.w += wt[i + 1] * __uint_as_float(v[i + 1].w);
                    }
                    acc.x += acd.x; acc.y += acd.y; acc.z += acd.z; acc.w += acd.w;
                    TL3(6, 0);
                    if (lane == 0) reinterpret_cast<float2*>(red + 1024)[x] = make_float2(mx, ll);
                    reinterpret_cast<float4*>(red)[tid] = acc;
                    const int d = kperm(16 * ((tid >> 2) & 3) + 8 * (tid & 1) + 64 * ((tid >> 1) & 1) + ((tid >> 4) & 7));
                    uint32_t od = sb + OFF_SS + 15 * 288 + 2 * d, ra = sb + OFF_SS + 8448;
                    asm volatile("" : "+r"(od), "+r"(ra));
                    bar_sync(2, 256);
                    if (x < 4) {
                        uint4 st[4];
                        float r[8];
#pragma unroll
                        for (int i = 0; i < 4; i++) st[i] = lds128(ra + 4096 + 16 * i);
#pragma unroll
                        for (int i = 0; i < 8; i++) r[i] = lds32(ra + 512 * i + 4 * tid);
                        float m2[4];
#pragma unroll
                        for (int i = 0; i < 4; i++) m2[i] = fmaxf(__uint_as_float(st[i].x), __uint_as_float(st[i].z));
                        const float mm = fmaxf(fmaxf(m2[0], m2[1]), fmaxf(m2[2], m2[3]));
                        float s0 = 0.f, s1 = 0.f, l0 = 0.f, l1 = 0.f;
#pragma unroll
                        for (int i = 0; i < 4; i++) {
                            const float f0 = ex2((__uint_as_float(st[i].x) - mm) * LOG2E), f1 = ex2((__uint_as_float(st[i].z) - mm) * LOG2E);
                            s0 += f0 * r[2 * i]; s1 += f1 * r[2 * i + 1];
                            l0 += f0 * __uint_as_float(st[i].y); l1 += f1 * __uint_as_float(st[i].w);
                        }
                        float inv;
                        asm("rcp.approx.ftz.f32 %0, %1;" : "=f"(inv) : "f"(l0 + l1));
                        const uint32_t ob = pack_bf16((s0 + s1) * inv, 0.f);
                        if (pass) asm volatile("st.shared.u16 [%0], %1;" :: "r"(od), "h"((uint16_t)ob) : "memory");
                        else st_rlx(&H.S->vec[1][h][j][d], (ob << 16) | tag);
                    }
                    __syncwarp();
                    if (pass && lane == 0) mbar_arrive(bar_vec + 8);
                    TL3(7, 0);
                    if (!pass) bar_sync(2, 256);
                }
            }
        }
    }
}

typedef CUresult (*EncodeFn)(CUtensorMap*, CUtensorMapDataType, cuuint32_t, void*, const cuuint64_t*, const cuuint64_t*,
                             const cuuint32_t*, const cuuint32_t*, CUtensorMapInterleave, CUtensorMapSwizzle,
                             CUtensorMapL2promotion, CUtensorMapFloatOOBfill);

void encode2d(EncodeFn fn, CUtensorMap* tm, void* ptr, uint64_t cols, uint64_t rows, uint32_t box_rows) {
    const cuuint64_t dims[2] = {cols, rows};
    const cuuint64_t strides[1] = {cols * 2};
    const cuuint32_t box[2] = {64, box_rows};
    const cuuint32_t es[2] = {1, 1};
    fn(tm, CU_TENSOR_MAP_DATA_TYPE_BFLOAT16, 2, ptr, dims, strides, box, es, CU_TENSOR_MAP_INTERLEAVE_NONE,
       CU_TENSOR_MAP_SWIZZLE_128B, CU_TENSOR_MAP_L2_PROMOTION_NONE, CU_TENSOR_MAP_FLOAT_OOB_FILL_NONE);
}

}

extern "C" void kernel_launch(void* const* d_in, const int* in_sizes, int n_in, void* d_out, int out_size) {
    (void)in_sizes; (void)n_in; (void)out_size;
    static EncodeFn encode = nullptr;
    static Scratch* scratch = nullptr;
    if (!encode) {
        cudaFuncSetAttribute(fused_decode_kernel, cudaFuncAttributeMaxDynamicSharedMemorySize, SMEM_BYTES + SMEM_EXTRA);
        void* fn = nullptr;
        cudaDriverEntryPointQueryResult qr;
        cudaGetDriverEntryPoint("cuTensorMapEncodeTiled", &fn, cudaEnableDefault, &qr);
        encode = (EncodeFn)fn;
        void* sp = nullptr;
        cudaGetSymbolAddress(&sp, g_scratch);
        scratch = (Scratch*)sp;
    }
    Params p;
    encode2d(encode, &p.tm_wq[0], d_in[9], 4096, 512, 128);
    encode2d(encode, &p.tm_wq[1], d_in[2], 4096, 512, 128);
    encode2d(encode, &p.tm_wuk,   d_in[3], 4096, 512, 128);
    encode2d(encode, &p.tm_wuv,   d_in[4], 4096, 512, 128);
    encode2d(encode, &p.tm_wo[1], d_in[10], 512, 4096, 128);
    encode2d(encode, &p.tm_wo[0], d_in[5], 512, 4096, 128);
    {
        const cuuint64_t dims[3] = {64, 16384, 8};
        const cuuint64_t strides[2] = {1024, 128};
        const cuuint32_t box[3] = {64, 16, 8};
        const cuuint32_t es[3] = {1, 1, 1};
        encode(&p.tm_ckv, CU_TENSOR_MAP_DATA_TYPE_BFLOAT16, 3, d_in[1], dims, strides, box, es, CU_TENSOR_MAP_INTERLEAVE_NONE,
               CU_TENSOR_MAP_SWIZZLE_128B, CU_TENSOR_MAP_L2_PROMOTION_NONE, CU_TENSOR_MAP_FLOAT_OOB_FILL_NONE);
    }
    p.wo[0] = (const __nv_bfloat16*)d_in[5];
    p.wo[1] = (const __nv_bfloat16*)d_in[10];
    p.out = (__nv_bfloat16*)d_out;
    Hot hp;
    hp.kp = (const char*)d_in[7];
    hp.vp = (const char*)d_in[8];
    hp.S = scratch;
    hp.x[0] = (const __nv_bfloat16*)d_in[6];
    hp.x[1] = (const __nv_bfloat16*)d_in[0];
    hp.zero = 0;
    hp.never = 0;
    cudaLaunchConfig_t cfg = {};
    cfg.gridDim = dim3(NCTA);
    cfg.blockDim = dim3(NTHREADS);
    cfg.dynamicSmemBytes = SMEM_BYTES + SMEM_EXTRA;
    cfg.stream = cudaStreamPerThread;
    cudaLaunchAttribute at[1];
    at[0].id = cudaLaunchAttributeCooperative;
    at[0].val.cooperative = 1;
    cfg.attrs = at;
    cfg.numAttrs = 1;
    cudaLaunchKernelEx(&cfg, fused_decode_kernel, hp, p);
}
```

```cpp
#include <cuda_runtime.h>
#include <cuda.h>
#include <cuda_bf16.h>
#include <stdint.h>

namespace {

constexpr int NCTA      = 128;
constexpr int NTHREADS  = 512;
constexpr int CH_BYTES  = 16384;
constexpr int NPIECE    = 128 * 64;
constexpr int RING      = 8;
#define PFV 10240
#define WIN 3
#define DL0 3250
#define DLS 1000
#define NB2 4650
#define NBS 1300
#define DLR 18
#define HS 31
#define XS 224
#define TG 5700
#define LAG 192
#define LAG2 96
#define LAG1 192
#define HURG 24
#define FSLEEP 600
#define QSLEEP 400
#define QD0 600
#define QD1 100
#define TRIG0 (20 * 128)
#define TRIG1 (32 * 128)
#define TRIG2 (50 * 128)
constexpr int SMEM_EXTRA = 0;
constexpr int A_SPLITS  = 8;
constexpr int A_TILES   = 4096 / A_SPLITS / 16;

constexpr int OFF_RING  = 0;
constexpr int OFF_XR    = OFF_RING + RING * CH_BYTES;
constexpr int OFF_SS    = OFF_XR + 4 * CH_BYTES;
constexpr int OFF_SP    = OFF_SS + 8 * 32 * 80;
constexpr int OFF_ALPHA = OFF_SP + 1024;
constexpr int OFF_OA    = OFF_ALPHA + 128;
constexpr int OFF_ST    = OFF_OA + 4 * 288;
constexpr int OFF_MLA   = OFF_ST + 64 * 32;
constexpr int OFF_QT    = OFF_MLA + 4 * A_SPLITS * 8;
constexpr int MG_BYTES  = 2048 + 128 + 32;
constexpr int OFF_MG    = OFF_QT + 4 * 256;
constexpr int OFF_META  = OFF_MG + 2 * MG_BYTES;
constexpr int OFF_EP    = OFF_META + 16;
constexpr int OFF_X     = OFF_SS + 4096;
constexpr int OFF_BAR   = OFF_EP + 16;
constexpr int NBAR      = 2 * RING + 8 + 2 + 3 + 4 + 3 + 1 + 8 + 8 + 2 + 2 + 2 + 1;
constexpr int I_INI     = 2 * RING + 8 + 2 + 3 + 4 + 3;
constexpr int SMEM_BYTES = OFF_BAR + NBAR * 8;

constexpr float LOG2E = 1.4426950408889634f;
constexpr float SCALE = 0.08838834764831845f;
constexpr uint32_t SPIN_LIMIT = 1u << 20;

struct Scratch {
    uint32_t ticket[2][64];
    uint32_t epoch[NCTA];
    uint32_t cntQ[64], cntA[64];
    float2   mlA[32][4][A_SPLITS];
    uint32_t vec[2][32][4][128];
    uint32_t q[2][4][4096];
    uint16_t qabs[4][8][2][4][2][32][8];
    float    pA[32][4][A_SPLITS][512];
    uint32_t pB[NPIECE][128];
    uint32_t mlB[NPIECE][8];
};
__device__ __align__(128) Scratch g_scratch;
#define TL(i) do {} while (0)
#define TL3(i, dep) do {} while (0)
#define TLG(i) do {} while (0)
#define TL2(i) do {} while (0)

struct Hot {
    const char *kp, *vp;
    Scratch* S;
    const __nv_bfloat16* x[2];
    uint32_t zero;
    uint32_t never;
};
struct Params {
    CUtensorMap tm_wq[2];
    CUtensorMap tm_wuk, tm_wuv;
    CUtensorMap tm_wo[2];
    CUtensorMap tm_ckv;
    const __nv_bfloat16* wo[2];
    __nv_bfloat16* out;
};

__device__ __forceinline__ void mbar_init(uint32_t bar, uint32_t cnt) {
    asm volatile("mbarrier.init.shared::cta.b64 [%0], %1;" :: "r"(bar), "r"(cnt) : "memory");
}
__device__ __forceinline__ void mbar_expect_tx(uint32_t bar, uint32_t bytes) {
    asm volatile("mbarrier.arrive.expect_tx.shared::cta.b64 _, [%0], %1;" :: "r"(bar), "r"(bytes) : "memory");
}
__device__ __forceinline__ void mbar_arrive(uint32_t bar) {
    asm volatile("mbarrier.arrive.shared::cta.b64 _, [%0];" :: "r"(bar) : "memory");
}
template <uint32_t LIMIT = SPIN_LIMIT>
__device__ __forceinline__ bool mbar_wait(uint32_t bar, uint32_t parity) {
    uint32_t done, it = 0;
    do {
        asm volatile("{\n.reg .pred p;\nmbarrier.try_wait.parity.shared::cta.b64 p, [%1], %2;\nselp.u32 %0, 1, 0, p;\n}"
                     : "=r"(done) : "r"(bar), "r"(parity) : "memory");
        if (++it > LIMIT) break;
    } while (!done);
    return done;
}
__device__ __forceinline__ void bulk_load(uint32_t dst, const void* src, uint32_t bytes, uint32_t bar, uint64_t pol) {
    asm volatile("cp.async.bulk.shared::cluster.global.mbarrier::complete_tx::bytes.L2::cache_hint [%0], [%1], %2, [%3], %4;"
                 :: "r"(dst), "l"(src), "r"(bytes), "r"(bar), "l"(pol) : "memory");
}
__device__ __forceinline__ uint64_t policy_evict_first() {
    uint64_t pol;
    asm volatile("createpolicy.fractional.L2::evict_first.b64 %0, 1.0;" : "=l"(pol));
    return pol;
}
__device__ __forceinline__ void bar_sync(int id, int n)   { asm volatile("bar.sync %0, %1;" :: "r"(id), "r"(n) : "memory"); }
__device__ __forceinline__ void bar_arrive(int id, int n) { asm volatile("bar.arrive %0, %1;" :: "r"(id), "r"(n) : "memory"); }
__device__ __forceinline__ void ldsm4(uint32_t (&r)[4], uint32_t addr) {
    asm volatile("ldmatrix.sync.aligned.m8n8.x4.shared.b16 {%0,%1,%2,%3}, [%4];"
                 : "=r"(r[0]), "=r"(r[1]), "=r"(r[2]), "=r"(r[3]) : "r"(addr) : "memory");
}
__device__ __forceinline__ void ldsm4t(uint32_t (&r)[4], uint32_t addr) {
    asm volatile("ldmatrix.sync.aligned.m8n8.x4.trans.shared.b16 {%0,%1,%2,%3}, [%4];"
                 : "=r"(r[0]), "=r"(r[1]), "=r"(r[2]), "=r"(r[3]) : "r"(addr) : "memory");
}
__device__ __forceinline__ void mma(float (&c)[4], uint32_t a0, uint32_t a1, uint32_t a2, uint32_t a3, uint32_t b0, uint32_t b1) {
    asm volatile("mma.sync.aligned.m16n8k16.row.col.f32.bf16.bf16.f32 {%0,%1,%2,%3}, {%4,%5,%6,%7}, {%8,%9}, {%0,%1,%2,%3};"
                 : "+f"(c[0]), "+f"(c[1]), "+f"(c[2]), "+f"(c[3])
                 : "r"(a0), "r"(a1), "r"(a2), "r"(a3), "r"(b0), "r"(b1));
}
__device__ __forceinline__ uint32_t prmt(uint32_t a, uint32_t b, uint32_t s) {
    uint32_t r; asm("prmt.b32 %0, %1, %2, %3;" : "=r"(r) : "r"(a), "r"(b), "r"(s)); return r;
}
__device__ __forceinline__ uint32_t pack_bf16(float lo, float hi) {
    uint32_t r; asm("cvt.rn.bf16x2.f32 %0, %1, %2;" : "=r"(r) : "f"(hi), "f"(lo)); return r;
}
__device__ __forceinline__ float bf16_round(float v) { return __uint_as_float(pack_bf16(0.f, v) & 0xffff0000u); }
__device__ __forceinline__ float ex2(float x) { float r; asm("ex2.approx.ftz.f32 %0, %1;" : "=f"(r) : "f"(x)); return r; }
__device__ __forceinline__ uint4 ld_rlx4(const void* p) {
    uint4 v;
    asm volatile("ld.relaxed.gpu.global.v4.u32 {%0,%1,%2,%3}, [%4];" : "=r"(v.x), "=r"(v.y), "=r"(v.z), "=r"(v.w) : "l"(p) : "memory");
    return v;
}
__device__ __forceinline__ uint32_t ld_acq(const void* p) {
    uint32_t v; asm volatile("ld.acquire.gpu.global.u32 %0, [%1];" : "=r"(v) : "l"(p) : "memory"); return v;
}
__device__ __forceinline__ void st_rlx(void* p, uint32_t v) { asm volatile("st.relaxed.gpu.global.u32 [%0], %1;" :: "l"(p), "r"(v) : "memory"); }
__device__ __forceinline__ void st_rlx4(void* p, uint32_t a, uint32_t b, uint32_t c, uint32_t d) {
    asm volatile("st.relaxed.gpu.global.v4.u32 [%0], {%1,%2,%3,%4};" :: "l"(p), "r"(a), "r"(b), "r"(c), "r"(d) : "memory");
}
__device__ __forceinline__ float warp_max(float v) {
    int k = __float_as_int(v);
    k ^= (k >> 31) & 0x7fffffff;
    k = __reduce_max_sync(0xffffffffu, k);
    k ^= (k >> 31) & 0x7fffffff;
    return __int_as_float(k);
}
__device__ __forceinline__ uint32_t tagf(float v, uint32_t par) { return (__float_as_uint(v) & ~1u) | par; }
__device__ __forceinline__ void wait_count(const uint32_t* c, uint32_t val, uint32_t sleep) {
#pragma unroll 1
    for (uint32_t it = 0; it < SPIN_LIMIT && ld_acq(c) != val; it++) __nanosleep(sleep);
}
__device__ __forceinline__ uint32_t take_ticket(uint32_t* c) {
    uint32_t v; asm volatile("atom.relaxed.gpu.global.add.u32 %0, [%1], 1;" : "=r"(v) : "l"(c) : "memory"); return v;
}
__device__ __forceinline__ void add_rel(uint32_t* c) { asm volatile("red.release.gpu.global.add.u32 [%0], 1;" :: "l"(c) : "memory"); }
__device__ __forceinline__ uint32_t tag16(uint32_t ep) { return (ep & 0x7fffu) | 0x8000u; }
__device__ __forceinline__ void gather128(const uint32_t* src, uint32_t tag, unsigned char* dst, int lane, uint32_t sleep) {
    uint4 v;
#pragma unroll 1
    for (uint32_t it = 0; it < SPIN_LIMIT; it++) {
        v = ld_rlx4(src + lane * 4);
        const bool ok = ((((v.x ^ tag) | (v.y ^ tag)) | ((v.z ^ tag) | (v.w ^ tag))) & 0xffffu) == 0;
        if (__all_sync(0xffffffffu, ok)) break;
        __nanosleep(sleep);
    }
    *reinterpret_cast<uint2*>(dst + lane * 8) = make_uint2(prmt(v.x, v.y, 0x7632), prmt(v.z, v.w, 0x7632));
}

__device__ __forceinline__ void bulk_load_nh(uint32_t dst, const void* src, uint32_t bytes, uint32_t bar) {
    asm volatile("cp.async.bulk.shared::cluster.global.mbarrier::complete_tx::bytes [%0], [%1], %2, [%3];"
                 :: "r"(dst), "l"(src), "r"(bytes), "r"(bar) : "memory");
}
__device__ __forceinline__ void tma2d_hint(uint32_t dst, const CUtensorMap* tm, int c0, int c1, uint32_t bar, uint64_t pol) {
    asm volatile("cp.async.bulk.tensor.2d.shared::cluster.global.mbarrier::complete_tx::bytes.L2::cache_hint [%0], [%1, {%3, %4}], [%2], %5;"
                 :: "r"(dst), "l"(tm), "r"(bar), "r"(c0), "r"(c1), "l"(pol) : "memory");
}
__device__ __forceinline__ void tma3d_hint(uint32_t dst, const CUtensorMap* tm, int c0, int c1, int c2, uint32_t bar, uint64_t pol) {
    asm volatile("cp.async.bulk.tensor.3d.shared::cluster.global.mbarrier::complete_tx::bytes.L2::cache_hint [%0], [%1, {%3, %4, %5}], [%2], %6;"
                 :: "r"(dst), "l"(tm), "r"(bar), "r"(c0), "r"(c1), "r"(c2), "l"(pol) : "memory");
}
__device__ __forceinline__ void prefetch32(const void* p) { asm volatile("cp.async.bulk.prefetch.L2.global [%0], 32;" :: "l"(p) : "memory"); }
__device__ __forceinline__ void prefetch_tm(const CUtensorMap* tm) { asm volatile("prefetch.tensormap [%0];" :: "l"(tm) : "memory"); }
__device__ __forceinline__ int kperm(int d) { return (d & ~15) | ((d & 6) << 1) | ((d >> 2) & 2) | (d & 1); }

template <int NK>
__device__ __forceinline__ uint32_t load_wT(uint32_t (&w)[NK][4][4], uint32_t base, int lane) {
    const int r8 = lane & 7;
    const uint32_t a0 = base + (r8 + 8 * (lane >> 4)) * 128 + ((((lane >> 3) & 1) ^ r8) << 4);
    uint32_t dep = 0;
#pragma unroll
    for (int s = 0; s < NK; s++)
#pragma unroll
        for (int mt = 0; mt < 4; mt++) { ldsm4t(w[s][mt], (a0 ^ (mt << 5)) + s * 2048); dep |= w[s][mt][0]; }
    return dep;
}

__device__ __forceinline__ bool mbar_test(uint32_t bar, uint32_t parity) {
    uint32_t done;
    asm volatile("{\n.reg .pred p;\nmbarrier.test_wait.parity.shared::cta.b64 p, [%1], %2;\nselp.u32 %0, 1, 0, p;\n}"
                 : "=r"(done) : "r"(bar), "r"(parity) : "memory");
    return done;
}
__device__ __forceinline__ void st_rlx2x64(void* p, uint32_t a, uint32_t b, uint32_t c, uint32_t d) {
    asm volatile("{\n.reg .b64 u, v;\nmov.b64 u, {%1,%2};\nmov.b64 v, {%3,%4};\nst.relaxed.gpu.global.v2.b64 [%0], {u, v};\n}"
                 :: "l"(p), "r"(a), "r"(b), "r"(c), "r"(d) : "memory");
}
__device__ __forceinline__ void ld_rlx2x64_if(uint4& v, const void* p, uint32_t pred) {
    asm volatile("{\n.reg .pred p;\n.reg .b64 u, v;\nsetp.ne.u32 p, %5, 0;\nmov.b64 u, {%0,%1};\nmov.b64 v, {%2,%3};\n"
                 "@p ld.relaxed.gpu.global.v2.b64 {u, v}, [%4];\nmov.b64 {%0,%1}, u;\nmov.b64 {%2,%3}, v;\n}"
                 : "+r"(v.x), "+r"(v.y), "+r"(v.z), "+r"(v.w) : "l"(p), "r"(pred) : "memory");
}
__device__ __forceinline__ uint4 lds128(uint32_t a) {
    uint4 v; asm volatile("ld.shared.v4.u32 {%0,%1,%2,%3}, [%4];" : "=r"(v.x), "=r"(v.y), "=r"(v.z), "=r"(v.w) : "r"(a) : "memory"); return v;
}
__device__ __forceinline__ float lds32(uint32_t a) { float v; asm volatile("ld.shared.f32 %0, [%1];" : "=f"(v) : "r"(a) : "memory"); return v; }
__device__ __forceinline__ uint32_t untagged(const uint4& v, uint32_t par) {
    uint32_t bad;
    asm("lop3.b32 %0, %1, %2, %3, 0x7e;" : "=r"(bad) : "r"(v.x), "r"(v.z), "r"(par));
    return bad;
}
__device__ __forceinline__ uint32_t or3(uint32_t a, uint32_t b, uint32_t c) {
    uint32_t r; asm("lop3.b32 %0, %1, %2, %3, 0xfe;" : "=r"(r) : "r"(a), "r"(b), "r"(c)); return r;
}
__device__ __forceinline__ void red_bf2(void* p, uint32_t v) {
    asm volatile("red.relaxed.gpu.global.add.noftz.bf16x2 [%0], %1;" :: "l"(p), "r"(v) : "memory");
}

__global__ void __launch_bounds__(NTHREADS, 1) fused_decode_kernel(const __grid_constant__ Hot H, const __grid_constant__ Params P) {
    asm volatile("{\n.reg .pred p;\nsetp.eq.u32 p, %2, 0;\n@p cp.async.bulk.prefetch.L2.global [%0], %1;\n}"
                 :: "l"(H.vp + (size_t)blockIdx.x * CH_BYTES), "n"(PFV), "r"(threadIdx.x) : "memory");
    if (H.never) return;
    const uint64_t pol = policy_evict_first();
    extern __shared__ __align__(1024) unsigned char smem[];
    const uint32_t sb = (uint32_t)__cvta_generic_to_shared(smem);
    const int bid = blockIdx.x, h = bid >> 2, j = bid & 3;
    const int lane = threadIdx.x & 31;
    const int g = lane >> 2, t = lane & 3;
    const uint32_t bar_full = sb + OFF_BAR, bar_empty = bar_full + RING * 8;
    const uint32_t bar_xfull = bar_empty + RING * 8, bar_xempty = bar_xfull + 32, bar_vec = bar_xempty + 32, bar_trig = bar_vec + 16;
    const uint32_t bar_wo = bar_trig + 24, bar_cmb = bar_wo + 32, bar_ini = bar_cmb + 24, bar_gat = bar_ini + 8, bar_qreq = bar_gat + 64, bar_qfull = bar_qreq + 32;
    const uint32_t bar_mempty = bar_qfull + 32, bar_mfull = bar_mempty + 16;
    const uint32_t bar_sfull = bar_mfull + 16, bar_xdone = bar_sfull + 16;
    const int mat = bid & 1, cb = bid >> 1;
    const int ab = h & 3, asplit = h >> 2;
    const int br = j < 2, hp = h & 7, cbk = 2 * (h >> 3) + (j & 1);
    const int hl = br ? 24 + hp : 0;

    const char* kp = H.kp;
    const char* vp = H.vp;
    if (threadIdx.x == 0) {
        mbar_init(bar_full, 1);
        asm volatile("fence.mbarrier_init.release.cluster;" ::: "memory");
        mbar_expect_tx(bar_full, CH_BYTES);
        bulk_load(sb + OFF_RING, kp + bid * CH_BYTES, CH_BYTES, bar_full, pol);
        TL(0); TLG(0);
#pragma unroll
        for (int i = 0; i < 4; i++) mbar_init(bar_xfull + i * 8, 1);
        mbar_init(bar_full + 8, 1);
        mbar_init(bar_ini, 1);
        asm volatile("fence.mbarrier_init.release.cluster;" ::: "memory");
#pragma unroll
        for (int i = 0; i < 4; i++) {
            mbar_expect_tx(bar_xfull + i * 8, CH_BYTES);
            tma2d_hint(sb + OFF_XR + i * CH_BYTES, &P.tm_wq[mat], 64 * cb, 128 * i, bar_xfull + i * 8, pol);
            if (i == 0) {
                mbar_expect_tx(bar_full + 8, CH_BYTES);
                bulk_load(sb + OFF_RING + CH_BYTES, vp + bid * CH_BYTES, CH_BYTES, bar_full + 8, pol);
                mbar_expect_tx(bar_ini, 4096 + 16);
                bulk_load_nh(sb + OFF_EP, &H.S->epoch[4 * h], 16, bar_ini);
                bulk_load_nh(sb + OFF_X, H.x[mat], 4096, bar_ini);
            }
        }
        *reinterpret_cast<int*>(smem + OFF_META) = bid;
#pragma unroll
        for (int i = 2; i < NBAR; i++)
            if ((i < 2 * RING || i >= 2 * RING + 4) && i != I_INI)
                mbar_init(bar_full + i * 8, ((i >= RING && i < 2 * RING) || (i >= NBAR - 5 && i < NBAR - 1)) ? 4
                                          : (i >= 2 * RING + 4 && i < 2 * RING + 10) ? 8 : i == NBAR - 1 ? 9 : 1);
        asm volatile("fence.mbarrier_init.release.cluster;" ::: "memory");
        mbar_arrive(bar_qreq);
    }

    __syncwarp();
    const int warp = __shfl_sync(0xffffffffu, threadIdx.x >> 5, 0);
    auto epoch = [&]() -> uint32_t {
        mbar_wait(bar_ini, 0);
        return __shfl_sync(0xffffffffu, reinterpret_cast<const uint32_t*>(smem + OFF_EP)[j], 0) + 1;
    };

    if (warp >= 12) {
        asm volatile("setmaxnreg.dec.sync.aligned.u32 40;");
        bar_sync(1, 512);
        const uint32_t ep = epoch();
        if (warp == 12) {
            if (lane == 0) {
                uint32_t* tick = &H.S->ticket[ep & 1][threadIdx.x & H.zero];
                if (bid == 0) H.S->ticket[(ep & 1) ^ 1][0] = 0;
                int ntrig = 0, piece = bid, i = 2;
                uint32_t next = 0, tclaim = clock(), tg = 0;
#pragma unroll 1
                for (;; i++) {
                    const int s = i % RING;
                    if (i <= 4) mbar_wait<2048>(bar_xfull + (i - 2) * 8, 0);
                    if (i >= WIN) {
                        mbar_wait(bar_full + ((i - WIN) % RING) * 8, ((i - WIN) / RING) & 1);
                        if (i - WIN < 192) TL2(i - WIN);
                    }
                    if (i >= RING && !mbar_wait(bar_empty + s * 8, ((i / RING) - 1) & 1)) break;
                    if (!(i & 1)) {
                        piece = i == 2 ? NCTA + bid : 2 * NCTA + (int)next;
                        reinterpret_cast<volatile int*>(smem + OFF_META)[s >> 1] = piece < NPIECE ? piece : -1;
                        mbar_arrive(bar_qreq + (s >> 1) * 8);
                        while (ntrig < 3 && piece >= (ntrig == 0 ? TRIG0 : ntrig == 1 ? TRIG1 : TRIG2)) mbar_arrive(bar_trig + 8 * ntrig++);
                        if (piece >= NPIECE) break;
                        tg = tclaim + (NPIECE - piece) * DLR;
                    }
                    mbar_expect_tx(bar_full + s * 8, CH_BYTES);
                    bulk_load(sb + OFF_RING + s * CH_BYTES, ((i & 1) ? vp : kp) + (size_t)piece * CH_BYTES, CH_BYTES, bar_full + s * 8, pol);
                    if ((piece & 127) == 0 && piece + 2 * NCTA < NPIECE) prefetch32(((i & 1) ? vp : kp) + (size_t)(piece + 2 * NCTA) * CH_BYTES);
                    if ((piece >> 7) == 60) prefetch32(P.wo[br] + (hp + 16 * (i & 1)) * 65536 + 64 * cbk);
                    if (i & 1) {
                        if (hl >= HS && piece >= NPIECE - XS) next = NPIECE - 2 * NCTA;
                        else { next = take_ticket(tick); tclaim = clock(); }
                    }
                }
                mbar_wait(bar_xdone, 0);
                if (i >= RING) mbar_wait(bar_empty + (i % RING) * 8 + 8, ((i / RING) - 1) & 1);
                const int tlook = TG - (31 - hl) * 64 * DLR;
                bool look = hl >= HS;
                auto since = [&]() -> int {
                    const int now = (int)((uint32_t)clock() - tg);
                    if (look && now >= tlook) { mbar_arrive(bar_cmb + 16); look = false; }
                    return now;
                };
#pragma unroll 1
                for (int k = 0; k < 4; k++) {
                    const uint32_t dst = sb + (k < 2 ? OFF_RING + (i % RING) * CH_BYTES : OFF_XR) + k * CH_BYTES;
                    const int wi = k - 2;
                    const uint32_t wb = wi >= 0 ? bar_wo + wi * 8 : bar_full + ((i + wi) % RING) * 8, wp = wi >= 0 ? 0 : ((i + wi) / RING) & 1;
                    while (wi >= 0 && hl < HS && since() < NB2 + wi * NBS) {}
                    while (!mbar_test(wb, wp) && since() < DL0 + k * DLS) {}
                    mbar_expect_tx(bar_wo + k * 8, CH_BYTES);
                    tma2d_hint(dst, &P.tm_wo[br], 64 * cbk, (hp + 8 * k) * 128, bar_wo + k * 8, pol);
                }
                while (look) since();
                TL(1);
            }
        } else if (warp == 15) {
            const uint32_t par = ep & 1;
            const uint32_t t0 = 64 * (32 * j + h + 1) + LAG, t1 = 64 * (96 + (hl < HURG ? hl : hl - 8) + 1) + LAG + LAG1, t2 = 64 * (96 + hl + 1) + LAG2;
            uint32_t fired = 0;
#pragma unroll 1
            for (int r = 0;; r++) {
                const unsigned char* mg = smem + OFF_MG + (r & 1) * MG_BYTES;
                if (!mbar_wait(bar_sfull + (r & 1) * 8, (r >> 1) & 1)) break;
                const uint32_t piece = *reinterpret_cast<const uint32_t*>(mg + 2048 + 144);
                if (piece < NPIECE) {
                    const float4 mw = *reinterpret_cast<const float4*>(mg + 2048 + 128);
                    const float mm = fmaxf(fmaxf(mw.x, mw.y), fmaxf(mw.z, mw.w));
                    const float e0 = ex2((mw.x - mm) * LOG2E), e1 = ex2((mw.y - mm) * LOG2E);
                    const float e2 = ex2((mw.z - mm) * LOG2E), e3 = ex2((mw.w - mm) * LOG2E);
                    float l = reinterpret_cast<const float*>(mg + 2048)[lane] * ((lane & 16) ? ((lane & 8) ? e3 : e2) : ((lane & 8) ? e1 : e0));
#pragma unroll
                    for (int o = 16; o > 0; o >>= 1) l += __shfl_xor_sync(0xffffffffu, l, o);
                    uint32_t* dst = &H.S->pB[piece][lane * 4];
                    if (piece >= NPIECE - 512) mbar_wait(bar_xdone, 0);
                    if (lane < 2) st_rlx2x64(&H.S->mlB[piece][lane * 4], tagf(l, par), __float_as_uint(mm), par, 0);
                    mbar_wait(bar_mfull + (r & 1) * 8, (r >> 1) & 1);
                    const float4 a = reinterpret_cast<const float4*>(mg)[lane],      b = reinterpret_cast<const float4*>(mg)[32 + lane];
                    const float4 c = reinterpret_cast<const float4*>(mg)[64 + lane], d = reinterpret_cast<const float4*>(mg)[96 + lane];
                    st_rlx2x64(dst, tagf((a.x * e0 + b.x * e1) + (c.x * e2 + d.x * e3), par), __float_as_uint((a.y * e0 + b.y * e1) + (c.y * e2 + d.y * e3)),
                                    tagf((a.z * e0 + b.z * e1) + (c.z * e2 + d.z * e3), par), __float_as_uint((a.w * e0 + b.w * e1) + (c.w * e2 + d.w * e3)));
                    TL3(3, 0);
                }
                __syncwarp();
                const uint32_t now = (piece >= t0 ? 1u : 0u) | (piece >= t1 ? 2u : 0u) | (piece >= t2 && hl < HS ? 4u : 0u);
                if (lane < 3 && ((now & ~fired) >> lane & 1)) mbar_arrive(bar_cmb + lane * 8);
                fired = now;
                if (piece >= NPIECE) break;
                if (lane == 0) mbar_arrive(bar_mempty + (r & 1) * 8);
            }
        } else if (warp == 14) {
            mbar_wait<2048>(bar_xfull + 24, 0);
            __nanosleep(QD0);
#pragma unroll 1
            for (int r = 0;; r++) {
                if (!mbar_wait(bar_qreq + (r & 3) * 8, (r >> 2) & 1)) break;
                const int piece = reinterpret_cast<volatile int*>(smem + OFF_META)[r & 3];
                if (piece >= 0) gather128(&H.S->q[0][piece >> 11][((piece >> 6) & 31) * 128], tag16(ep), smem + OFF_QT + (r & 3) * 256, lane, QD1);
                __syncwarp();
                if (lane == 0) mbar_arrive(bar_qfull + (r & 3) * 8);
                if (piece < 0) break;
            }
        } else if (warp == 13) {
            if (lane == 0) { prefetch_tm(&P.tm_wuk); prefetch_tm(j == 0 ? &P.tm_ckv : &P.tm_wuv); }
            int n = 4;
            auto acquire = [&](uint32_t bytes) -> uint32_t {
                mbar_wait(bar_xempty + (n & 3) * 8, ((n >> 2) - 1) & 1);
                mbar_expect_tx(bar_xfull + (n & 3) * 8, bytes);
                return (uint32_t)(n++ & 3);
            };
            if (lane == 0) {
#pragma unroll 1
                for (int k = 0; k < 2; k++) {
                    const uint32_t s = acquire(CH_BYTES);
                    tma2d_hint(sb + OFF_XR + s * CH_BYTES, &P.tm_wuk, h * 128 + 64 * k, 128 * j, bar_xfull + s * 8, pol);
                }
                if (j >= 2) {
                    mbar_wait(bar_trig, 0);
#pragma unroll 1
                    for (int k = 0; k < 4; k++) {
                        const uint32_t s = acquire(CH_BYTES);
                        tma2d_hint(sb + OFF_XR + s * CH_BYTES, &P.tm_wuv, h * 128 + 64 * (j - 2), 128 * k, bar_xfull + s * 8, pol);
                    }
                }
            }
            __syncwarp();
            if (j == 0) bar_sync(10, 64);
            if (lane == 0) {
                if (j == 0) wait_count(H.S->cntQ, ep * NCTA, QSLEEP);
                else if (j >= 2) { mbar_wait(bar_trig + 8, 0); wait_count(H.S->cntA, ep * 4 * A_SPLITS, FSLEEP); }
                asm volatile("fence.proxy.async.global;" ::: "memory");
                if (j == 0) {
#pragma unroll 1
                    for (int k = 0; k < 4; k++) {
                        const uint32_t s = acquire(CH_BYTES);
                        bulk_load_nh(sb + OFF_XR + s * CH_BYTES, &H.S->qabs[ab][2 * k][0][0][0][0][0], CH_BYTES, bar_xfull + s * 8);
                    }
#pragma unroll 1
                    for (int k = 0; k < A_TILES; k++) {
                        const uint32_t s = acquire(CH_BYTES);
                        tma3d_hint(sb + OFF_XR + s * CH_BYTES, &P.tm_ckv, 0, ab * 4096 + 16 * (k * A_SPLITS + asplit), 0, bar_xfull + s * 8, pol);
                    }
                } else if (j >= 2) {
#pragma unroll 1
                    for (int k = 0; k < 4; k++) {
                        const uint32_t s = acquire(CH_BYTES + A_SPLITS * 8);
                        bulk_load_nh(sb + OFF_XR + s * CH_BYTES, &H.S->pA[h][k][0][0], CH_BYTES, bar_xfull + s * 8);
                        bulk_load_nh(sb + OFF_MLA + k * A_SPLITS * 8, &H.S->mlA[h][k][0], A_SPLITS * 8, bar_xfull + s * 8);
                    }
                }
            }
            __syncwarp();
            mbar_wait(bar_trig + 16, 0);
            if (lane == 0) {
                prefetch_tm(&P.tm_wo[br]);
                wait_count(H.S->cntQ, ep * NCTA, QSLEEP);
                mbar_arrive(bar_xdone);
            }
        }
    } else if (warp < 4) {
        asm volatile("setmaxnreg.dec.sync.aligned.u32 88;");
        bar_sync(1, 512);
        const uint32_t ep = epoch();
        const bool valid = (t == (g >> 1));
        const bool odd = g & 1;
        const int r8 = lane & 7;
        const uint32_t koff = (warp * 16 + r8 + 8 * ((lane >> 3) & 1)) * 256 + (((lane >> 4) ^ r8) << 4);
        const uint32_t voff = (warp * 16 + r8 + 8 * (lane >> 4)) * 256 + ((((lane >> 3) & 1) ^ r8) << 4);
        int r = 0;
#pragma unroll 1
        for (;; r++) {
            const int sk = (2 * r) % RING, sv = sk + 1;
            const uint32_t ph = ((2 * r) / RING) & 1;
            unsigned char* mg = smem + OFF_MG + (r & 1) * MG_BYTES;
            if (!mbar_wait(bar_qfull + (r & 3) * 8, ph)) break;
            if (r == 0 && threadIdx.x == 0) TL(4);
            const int piece = reinterpret_cast<volatile int*>(smem + OFF_META)[r & 3];
            if (piece < 0) {
                mbar_wait(bar_mempty + (r & 1) * 8, ((r >> 1) - 1) & 1);
                if (lane == 0) { *reinterpret_cast<int*>(mg + 2048 + 144) = piece; mbar_arrive(bar_sfull + (r & 1) * 8); }
                break;
            }
            uint32_t qf[16];
#pragma unroll
            for (int u = 0; u < 16; u++) qf[u] = reinterpret_cast<const uint32_t*>(smem + OFF_QT + (r & 3) * 256)[4 * (u ^ g) + t];
            mbar_wait(bar_full + sk * 8, ph);
            const uint32_t ka = sb + OFF_RING + sk * CH_BYTES + koff;
            float c0[4] = {0.f, 0.f, 0.f, 0.f}, c1[4] = {0.f, 0.f, 0.f, 0.f};
#pragma unroll
            for (int s = 0; s < 8; s += 2) {
                uint32_t a[4], b[4];
                ldsm4(a, ka ^ (s << 5));
                ldsm4(b, ka ^ ((s + 1) << 5));
                mma(c0, a[0], a[1], a[2], a[3], qf[2 * s], qf[2 * s + 1]);
                mma(c1, b[0], b[1], b[2], b[3], qf[2 * s + 2], qf[2 * s + 3]);
            }
            float slo = odd ? c0[1] + c1[1] : c0[0] + c1[0];
            float shi = odd ? c0[3] + c1[3] : c0[2] + c1[2];
            if (lane == 0) mbar_arrive(bar_empty + sk * 8 + (__float_as_uint(slo) & H.zero));
            slo = bf16_round(bf16_round(slo) * SCALE);
            shi = bf16_round(bf16_round(shi) * SCALE);
            const float m = warp_max(valid ? fmaxf(slo, shi) : -INFINITY);
            const float plo = valid ? ex2((slo - m) * LOG2E) : 0.f;
            const float phi = valid ? ex2((shi - m) * LOG2E) : 0.f;
            if (r >= 2) mbar_wait(bar_mempty + (r & 1) * 8, ((r >> 1) - 1) & 1);
            if (valid) reinterpret_cast<float*>(mg + 2048)[warp * 8 + g] = plo + phi;
            if (lane == 0) { reinterpret_cast<float*>(mg + 2048 + 128)[warp] = m; *reinterpret_cast<int*>(mg + 2048 + 144) = piece; }
            __syncwarp();
            if (lane == 0) mbar_arrive(bar_sfull + (r & 1) * 8);
            const uint32_t b0 = odd ? pack_bf16(0.f, plo) : pack_bf16(plo, 0.f);
            const uint32_t b1 = odd ? pack_bf16(0.f, phi) : pack_bf16(phi, 0.f);
            mbar_wait(bar_full + sv * 8, ph);
            if (warp == 0) TL3(0, 0);
            const uint32_t va = sb + OFF_RING + sv * CH_BYTES + voff;
            float ev[8], od[8];
#pragma unroll
            for (int i = 0; i < 8; i++) {
                uint32_t a[4];
                float acc[4] = {0.f, 0.f, 0.f, 0.f};
                ldsm4t(a, va ^ (i << 5));
                mma(acc, a[0], a[1], a[2], a[3], b0, b1);
                ev[i] = acc[0] + acc[3]; od[i] = acc[1] + acc[2];
            }
#pragma unroll
            for (int i = 0; i < 8; i += 2) {
                ev[i] += __shfl_xor_sync(0xffffffffu, ev[i + 1], 1);
                od[i] += __shfl_xor_sync(0xffffffffu, od[i + 1], 1);
            }
#pragma unroll
            for (int i = 0; i < 8; i += 4) {
                ev[i] += __shfl_xor_sync(0xffffffffu, ev[i + 2], 2);
                od[i] += __shfl_xor_sync(0xffffffffu, od[i + 2], 2);
            }
            reinterpret_cast<float4*>(mg)[warp * 32 + lane] = make_float4(ev[0], od[0], ev[4], od[4]);
            __syncwarp();
            if (lane == 0) {
                mbar_arrive(bar_mfull + (r & 1) * 8);
                mbar_arrive(bar_empty + sv * 8 + ((__float_as_uint(ev[0]) | __float_as_uint(ev[4])) & H.zero));
            }
        }
        TL3(2, 0);
        {
            int lane2 = lane;
            asm volatile("" : "+r"(lane2));
            const int g2 = lane2 >> 2;
            uint16_t* outp = reinterpret_cast<uint16_t*>(P.out) + (lane2 & 3) * 1024 + 512 * br + 64 * cbk + 16 * warp + ((g2 & 1) ? g2 + 7 : g2);
            const uint32_t sel = (g2 & 1) ? 0x3276 : 0x5410;
            const uint32_t aoff = (r8 + 8 * (lane2 >> 4)) * 128 + (((2 * warp + ((lane2 >> 3) & 1)) ^ r8) << 4);
            uint32_t a0 = sb + OFF_RING + ((2 * r) % RING) * CH_BYTES + aoff;
            uint32_t vp0 = sb + OFF_SS + (g2 >> 1) * 288 + 8 * (lane2 & 3);
            float d[4][4];
#pragma unroll
            for (int u = 0; u < 4; u++) d[u][0] = d[u][1] = d[u][2] = d[u][3] = 0.f;
            uint2 ob[8];
            auto load_v = [&]() {
#pragma unroll
                for (int s = 0; s < 8; s++)
                    asm volatile("ld.shared.v2.u32 {%0,%1}, [%2];" : "=r"(ob[s].x), "=r"(ob[s].y) : "r"(vp0 + 32 * s) : "memory");
            };
            uint32_t wf[8][4];
            auto load_w = [&]() {
#pragma unroll
                for (int s = 0; s < 8; s++) ldsm4t(wf[s], a0 + s * 2048);
            };
            auto mmas = [&]() {
#pragma unroll
                for (int s = 0; s < 8; s++) mma(d[s & 3], wf[s][0], wf[s][1], wf[s][2], wf[s][3], ob[s].x, ob[s].y);
            };
            int k = 0;
#pragma unroll 1
            for (;;) {
                mbar_wait(bar_wo + k * 8, 0);
                load_w();
                mbar_wait(bar_vec + (k ? 8 : 0), 0);
                load_v();
                mmas();
                if (k) break;
                a0 += CH_BYTES;
                vp0 += 4 * 288;
#pragma unroll 1
                for (k = 1;;) {
                    load_v();
                    uint32_t dep = 0;
#pragma unroll
                    for (int s = 0; s < 8; s++) dep |= ob[s].x;
                    a0 += dep & H.zero;
                    mbar_wait(bar_wo + k * 8, 0);
                    load_w();
                    mmas();
                    if (k == 3) goto done;
                    const bool have = k == 1 || mbar_test(bar_vec + 8, 0);
                    a0 = k == 1 ? sb + OFF_XR + 2 * CH_BYTES + aoff : a0 + CH_BYTES;
                    vp0 += 4 * 288;
                    k++;
                    if (!have) break;
                }
            }
        done:
            const uint32_t e = pack_bf16((d[0][0] + d[1][0]) + (d[2][0] + d[3][0]), (d[0][2] + d[1][2]) + (d[2][2] + d[3][2]));
            red_bf2(outp, prmt(e, __shfl_xor_sync(0xffffffffu, e, 4), sel));
            TL3(12, 0);
        }
    } else {
        asm volatile("setmaxnreg.inc.sync.aligned.u32 192;");
        const int x = warp - 4, tid = threadIdx.x - 128;
        bar_sync(1, 512);
        const uint32_t ep = epoch();
        const uint32_t tag = tag16(ep), par = ep & 1;
        uint32_t* qdst = &H.S->q[mat][tid >> 6][mat ? kperm(64 * cb + (tid & 63)) : 64 * cb + (tid & 63)];
        st_rlx(qdst, 0);
        if (j >= 2) st_rlx(&H.S->vec[0][h][tid >> 6][kperm(64 * (j - 2) + (tid & 63))], 0);
        if (tid < 128) st_rlx(&H.S->vec[1][h][j][tid], 0);
        if (tid < 16) reinterpret_cast<uint32_t*>(P.out)[bid * 16 + tid] = 0u;
        if (!mat) {
            st_rlx4(&H.S->pB[NPIECE - 512 + 8 * cb + x][lane * 4], par ^ 1, par ^ 1, par ^ 1, par ^ 1);
            if (lane < 2) st_rlx4(&H.S->mlB[NPIECE - 512 + 8 * cb + x][lane * 4], par ^ 1, par ^ 1, par ^ 1, par ^ 1);
        }
        const uint32_t xr = sb + OFF_XR;
        auto xwait = [&](int n) { mbar_wait(bar_xfull + (n & 3) * 8, (n >> 2) & 1); };
        auto xrel  = [&](int n, uint32_t dep) { if (lane == 0) mbar_arrive(bar_xempty + (n & 3) * 8 + (dep & H.zero)); };
        float* red = reinterpret_cast<float*>(smem + OFF_SS + 8448);
        {
            uint32_t w[4][4][4], xb[4][2];
#pragma unroll
            for (int s = 0; s < 4; s++) {
                const uint32_t* X = reinterpret_cast<const uint32_t*>(smem + OFF_X) + (g & 3) * 256 + 32 * x + 8 * s + t;
                xb[s][0] = X[0]; xb[s][1] = X[4];
            }
            xwait(x >> 1);
            const uint32_t dep = load_wT<4>(w, xr + x * 8192, lane);
            float acc[4][4];
#pragma unroll
            for (int u = 0; u < 4; u++) acc[u][0] = acc[u][1] = acc[u][2] = acc[u][3] = 0.f;
#pragma unroll
            for (int s = 0; s < 4; s++)
#pragma unroll
                for (int mt = 0; mt < 4; mt++) mma(acc[mt], w[s][mt][0], w[s][mt][1], w[s][mt][2], w[s][mt][3], xb[s][0], xb[s][1]);
#pragma unroll
            for (int n = 0; n < 4; n++) xrel(n, dep);
            if (t < 2) {
#pragma unroll
                for (int mt = 0; mt < 4; mt++) {
                    float* r0 = red + (x * 4 + 2 * t) * 64 + 16 * mt + g;
                    r0[0] = acc[mt][0]; r0[8] = acc[mt][2]; r0[64] = acc[mt][1]; r0[72] = acc[mt][3];
                }
            }
            bar_sync(2, 256);
            float s = 0.f;
#pragma unroll
            for (int i = 0; i < 8; i++) s += red[i * 256 + tid];
            st_rlx(qdst, (pack_bf16(0.f, s) & 0xffff0000u) | tag);
        }
        if (tid == 0) TL(6);
        {
            uint32_t w[8][4];
            const int r8 = lane & 7;
            const uint32_t a0 = xr + (16 * x + r8 + 8 * ((lane >> 3) & 1)) * 128 + (((lane >> 4) ^ r8) << 4);
#pragma unroll
            for (int hf = 0; hf < 2; hf++) {
                xwait(4 + hf);
                uint32_t dep = 0;
#pragma unroll
                for (int ks = 0; ks < 4; ks++) { ldsm4(w[4 * hf + ks], (a0 ^ (ks << 5)) + hf * CH_BYTES); dep |= w[4 * hf + ks][0]; }
                xrel(4 + hf, dep);
            }
            if (x < 4) gather128(&H.S->q[1][x][h * 128], tag, smem + OFF_OA + x * 288, lane, QD1);
            bar_sync(2, 256);
            float c[4] = {0.f, 0.f, 0.f, 0.f};
#pragma unroll
            for (int i = 0; i < 8; i++) {
                const uint2 b = *reinterpret_cast<const uint2*>(smem + OFF_OA + (g & 3) * 288 + (16 * i + 4 * t) * 2);
                mma(c, w[i][0], w[i][1], w[i][2], w[i][3], b.x, b.y);
            }
            uint16_t* stg = reinterpret_cast<uint16_t*>(smem + OFF_SS);
            if (t < 2) {
                const int ks = x & 3;
#pragma unroll
                for (int q = 0; q < 4; q++) {
                    const int b = 2 * t + (q & 1), rg = q >> 1;
                    const float vh = bf16_round(c[q]);
                    const int o = b * 256 + (x >> 2) * 128 + (ks >> 1) * 32 + (g >> 1) * 8 + (ks & 1) * 4 + rg * 2 + (g & 1);
                    stg[o]      = (uint16_t)(__float_as_uint(vh) >> 16);
                    stg[o + 64] = (uint16_t)pack_bf16(c[q] - vh, 0.f);
                }
            }
            bar_sync(2, 256);
            if (tid < 128) {
                const uint4 val = reinterpret_cast<const uint4*>(stg)[tid];
                *reinterpret_cast<uint4*>(&H.S->qabs[tid >> 5][2 * j + ((tid >> 4) & 1)][(tid >> 3) & 1][h >> 3][(tid >> 2) & 1][(h & 7) * 4 + (tid & 3)][0]) = val;
            }
            bar_sync(2, 256);
            if (tid == 0) { add_rel(H.S->cntQ); TL(7); }
            if (j == 0 && x == 0) bar_arrive(10, 64);
        }
        if (j == 0) {
            uint32_t qf[2][4][8];
#pragma unroll
            for (int k = 0; k < 4; k++) {
                xwait(6 + k);
                uint32_t dep = 0;
                if (k == (x >> 1)) {
                    const unsigned char* qp = smem + OFF_XR + ((6 + k) & 3) * CH_BYTES + (x & 1) * 8192 + lane * 16;
#pragma unroll
                    for (int i = 0; i < 16; i++) {
                        const uint4 a = *reinterpret_cast<const uint4*>(qp + i * 512);
                        uint32_t* d = &qf[i >> 3][(i >> 1) & 3][4 * (i & 1)];
                        d[0] = a.x; d[1] = a.y; d[2] = a.z; d[3] = a.w;
                        dep |= a.x;
                    }
                }
                xrel(6 + k, dep);
            }
            if (tid == 0) TL(8);
            float acc[4][4][4];
#pragma unroll
            for (int a = 0; a < 4; a++)
#pragma unroll
                for (int b = 0; b < 4; b++) acc[a][b][0] = acc[a][b][1] = acc[a][b][2] = acc[a][b][3] = 0.f;
            float m = -INFINITY, l = 0.f;
            const int r8 = lane & 7;
            const uint32_t koff = x * 2048 + (r8 + 8 * ((lane >> 3) & 1)) * 128 + (((lane >> 4) ^ r8) << 4);
            const uint32_t voff = x * 2048 + (r8 + 8 * (lane >> 4)) * 128 + ((((lane >> 3) & 1) ^ r8) << 4);
            const int sh = tid >> 3, skp = tid & 7;
#define CK0
#define CK1(v)
            for (int n = 10; n < 10 + A_TILES; n++) {
                CK0
                xwait(n);
                CK1(cw)
                const uint32_t base = xr + (n & 3) * CH_BYTES;
                float S[4][4];
#pragma unroll
                for (int nt = 0; nt < 4; nt++) S[nt][0] = S[nt][1] = S[nt][2] = S[nt][3] = 0.f;
#pragma unroll
                for (int ks = 0; ks < 4; ks++) {
                    uint32_t a[4];
                    ldsm4(a, base + (koff ^ (ks << 5)));
#pragma unroll
                    for (int nt = 0; nt < 4; nt++) mma(S[nt], a[0], a[1], a[2], a[3], qf[1][nt][2 * ks], qf[1][nt][2 * ks + 1]);
#pragma unroll
                    for (int nt = 0; nt < 4; nt++) mma(S[nt], a[0], a[1], a[2], a[3], qf[0][nt][2 * ks], qf[0][nt][2 * ks + 1]);
                }
#pragma unroll
                for (int nt = 0; nt < 4; nt++) {
                    unsigned char* sp = smem + OFF_SS + (x * 32 + 8 * nt + 2 * t) * 80 + 8 * g;
                    *reinterpret_cast<float2*>(sp) = make_float2(S[nt][0], S[nt][2]);
                    *reinterpret_cast<float2*>(sp + 80) = make_float2(S[nt][1], S[nt][3]);
                }
                bar_sync(2, 256);
                CK1(c1)
                float s0 = 0.f, s1 = 0.f;
#pragma unroll
                for (int w = 0; w < 8; w++) {
                    const float2 v = *reinterpret_cast<const float2*>(smem + OFF_SS + (w * 32 + sh) * 80 + 8 * skp);
                    s0 += v.x; s1 += v.y;
                }
                s0 = bf16_round(bf16_round(s0) * SCALE);
                s1 = bf16_round(bf16_round(s1) * SCALE);
                float mx = fmaxf(s0, s1);
                mx = fmaxf(mx, __shfl_xor_sync(0xffffffffu, mx, 1));
                mx = fmaxf(mx, __shfl_xor_sync(0xffffffffu, mx, 2));
                mx = fmaxf(mx, __shfl_xor_sync(0xffffffffu, mx, 4));
                mx = fmaxf(mx, m);
                const float al = ex2((m - mx) * LOG2E);
                m = mx;
                const float p0 = ex2((s0 - m) * LOG2E), p1 = ex2((s1 - m) * LOG2E);
                l = l * al + p0 + p1;
                {
                    const uint32_t pp = pack_bf16(p0, p1);
                    uint16_t* dst = reinterpret_cast<uint16_t*>(smem + OFF_SP) + sh * 16 + kperm(skp);
                    dst[0] = (uint16_t)pp; dst[2] = (uint16_t)(pp >> 16);
                }
                if (skp == 0) reinterpret_cast<float*>(smem + OFF_ALPHA)[sh] = al;
                bar_sync(2, 256);
                CK1(c2)
                uint2 pb[4];
#pragma unroll
                for (int nt = 0; nt < 4; nt++) {
                    pb[nt] = *reinterpret_cast<const uint2*>(smem + OFF_SP + (8 * nt + g) * 32 + 8 * t);
                    const float2 a2 = *reinterpret_cast<const float2*>(smem + OFF_ALPHA + (8 * nt + 2 * t) * 4);
#pragma unroll
                    for (int mt = 0; mt < 4; mt++) {
                        acc[mt][nt][0] *= a2.x; acc[mt][nt][1] *= a2.y; acc[mt][nt][2] *= a2.x; acc[mt][nt][3] *= a2.y;
                    }
                }
                uint32_t dep = 0;
#pragma unroll
                for (int mt = 0; mt < 4; mt++) {
                    uint32_t a[4];
                    ldsm4t(a, base + (voff ^ (mt << 5)));
                    dep |= a[0];
#pragma unroll
                    for (int nt = 0; nt < 4; nt++) mma(acc[mt][nt], a[0], a[1], a[2], a[3], pb[nt].x, pb[nt].y);
                }
                xrel(n, dep);
                CK1(c3)
            }
#pragma unroll
            for (int nt = 0; nt < 4; nt++)
#pragma unroll
                for (int e = 0; e < 2; e++) {
                    float* dst = &H.S->pA[8 * nt + 2 * t + e][ab][asplit][64 * x + 4 * g];
                    *reinterpret_cast<float4*>(dst)      = make_float4(acc[0][nt][e], acc[0][nt][2 + e], acc[1][nt][e], acc[1][nt][2 + e]);
                    *reinterpret_cast<float4*>(dst + 32) = make_float4(acc[2][nt][e], acc[2][nt][2 + e], acc[3][nt][e], acc[3][nt][2 + e]);
                }
            l += __shfl_xor_sync(0xffffffffu, l, 1);
            l += __shfl_xor_sync(0xffffffffu, l, 2);
            l += __shfl_xor_sync(0xffffffffu, l, 4);
            if (skp == 0) H.S->mlA[sh][ab][asplit] = make_float2(m, l);
            bar_sync(2, 256);
            if (tid == 0) { add_rel(H.S->cntA); TL(9); }
        } else if (j >= 2) {
            uint32_t wv[4][4][4];
#pragma unroll
            for (int k = 0; k < 4; k++) {
                xwait(6 + k);
                uint32_t dep = 0;
                if (k == (x >> 1)) dep = load_wT<4>(wv, xr + ((6 + k) & 3) * CH_BYTES + (x & 1) * 8192, lane);
                xrel(6 + k, dep);
            }
            {
                const int b = tid >> 6, xx = (tid >> 3) & 7, gg = tid & 7;
                xwait(10 + b);
                if (tid == 0) TL(8);
                const float2* mlp = reinterpret_cast<const float2*>(smem + OFF_MLA) + b * A_SPLITS;
                float mm = -INFINITY, ll = 0.f;
#pragma unroll
                for (int s = 0; s < A_SPLITS; s++) mm = fmaxf(mm, mlp[s].x);
#pragma unroll
                for (int s = 0; s < A_SPLITS; s++) ll += mlp[s].y * ex2((mlp[s].x - mm) * LOG2E);
                const float inv = 1.f / ll;
                float cl[8];
#pragma unroll
                for (int e = 0; e < 8; e++) cl[e] = 0.f;
                const float* src = reinterpret_cast<const float*>(smem + OFF_XR + ((10 + b) & 3) * CH_BYTES) + 64 * xx + 4 * gg;
#pragma unroll
                for (int s = 0; s < A_SPLITS; s++) {
                    const float wt = ex2((mlp[s].x - mm) * LOG2E) * inv;
                    const float4 a = *reinterpret_cast<const float4*>(src + s * 512), c = *reinterpret_cast<const float4*>(src + s * 512 + 32);
                    cl[0] += wt * a.x; cl[1] += wt * a.y; cl[2] += wt * a.z; cl[3] += wt * a.w;
                    cl[4] += wt * c.x; cl[5] += wt * c.y; cl[6] += wt * c.z; cl[7] += wt * c.w;
                }
                uint16_t* hi = reinterpret_cast<uint16_t*>(smem + OFF_SS + b * 1056);
                uint16_t* lo = reinterpret_cast<uint16_t*>(smem + OFF_SS + (b + 4) * 1056);
#pragma unroll
                for (int e = 0; e < 8; e++) {
                    const int c = kperm(64 * xx + 8 * e + gg);
                    const float vh = bf16_round(cl[e]);
                    hi[c] = (uint16_t)(__float_as_uint(vh) >> 16);
                    lo[c] = (uint16_t)pack_bf16(cl[e] - vh, 0.f);
                }
                bar_sync(2, 256);
#pragma unroll
                for (int k = 0; k < 4; k++) xrel(10 + k, __float_as_uint(cl[0]) | __float_as_uint(cl[4]));
            }
            {
                float acc[4][4];
#pragma unroll
                for (int u = 0; u < 4; u++) acc[u][0] = acc[u][1] = acc[u][2] = acc[u][3] = 0.f;
#pragma unroll
                for (int s = 0; s < 4; s++) {
                    const uint2 b = *reinterpret_cast<const uint2*>(smem + OFF_SS + g * 1056 + (64 * x + 16 * s + 4 * t) * 2);
#pragma unroll
                    for (int mt = 0; mt < 4; mt++) mma(acc[mt], wv[s][mt][0], wv[s][mt][1], wv[s][mt][2], wv[s][mt][3], b.x, b.y);
                }
#pragma unroll
                for (int mt = 0; mt < 4; mt++)
#pragma unroll
                    for (int e = 0; e < 4; e++) acc[mt][e] += __shfl_xor_sync(0xffffffffu, acc[mt][e], 2);
                if (t < 2) {
#pragma unroll
                    for (int mt = 0; mt < 4; mt++) {
                        float* r0 = red + (x * 4 + 2 * t) * 64 + 16 * mt + g;
                        r0[0] = acc[mt][0]; r0[8] = acc[mt][2]; r0[64] = acc[mt][1]; r0[72] = acc[mt][3];
                    }
                }
            }
            bar_sync(2, 256);
            {
                float s = 0.f;
#pragma unroll
                for (int i = 0; i < 8; i++) s += red[i * 256 + tid];
                st_rlx(&H.S->vec[0][h][tid >> 6][kperm(64 * (j - 2) + (tid & 63))], (pack_bf16(0.f, s) & 0xffff0000u) | tag);
            }
            if (tid == 0) TL(9);
        }
        {
            __syncwarp();
            if (lane == 0) mbar_arrive(bar_xdone);
#pragma unroll 1
            for (uint32_t pass = H.zero; pass < 2; pass++) {
                if (pass == br) {
                    mbar_wait(br ? bar_cmb + 8 : bar_trig + 16, 0);
#pragma unroll 1
                    for (int u = 2 * x; u < 2 * x + 2; u++)
                        if (u < 15 || hl < HURG) gather128(&H.S->vec[br][hp + 8 * (u >> 2)][u & 3][0], tag, smem + OFF_SS + u * 288, lane, QD1);
                    __syncwarp();
                    if (lane == 0) { mbar_arrive(bar_vec); if (hl < HURG) mbar_arrive(bar_vec + 8); }
                    TL3(13, 0);
                    if (tid == 0) { H.S->epoch[bid] = ep; TL(10); }
                }
                if (pass ? hl >= HURG : (j < 3 || h < HURG)) {
                    const int pr = pass ? 96 + hl : 32 * j + h;
                    const uint32_t* rp = &H.S->pB[64 * pr + 8 * x][lane * 4];
                    const uint32_t* sp = &H.S->mlB[64 * pr + 8 * x + (lane & 7)][0];
                    uint4 v[8], sv;
                    mbar_wait(bar_cmb + pass * 16, 0);
                    TL3(5, 0);
                    if (lane == 0) {
                        mbar_expect_tx(bar_gat + x * 8, 4096 + 256);
                        bulk_load_nh(xr + x * 4096, rp, 4096, bar_gat + x * 8);
                        bulk_load_nh(sb + OFF_ST + x * 256, sp, 256, bar_gat + x * 8);
                    }
                    __syncwarp();
                    mbar_wait(bar_gat + x * 8, pass);
                    TL3(15, 0);
                    sv = lds128(sb + OFF_ST + x * 256 + (lane & 7) * 32);
#pragma unroll
                    for (int i = 0; i < 8; i++) v[i] = lds128(xr + x * 4096 + i * 512 + lane * 16);
                    float mx, ll, wt[8];
#pragma unroll 1
                    for (uint32_t it = 0;; it++) {
                        uint32_t bad[9];
#pragma unroll
                        for (int i = 0; i < 8; i++) bad[i] = untagged(v[i], par);
                        bad[8] = untagged(sv, par);
                        const uint32_t anyb = or3(or3(bad[0], bad[1], bad[2]), or3(bad[3], bad[4], bad[5]), or3(bad[6], bad[7], bad[8]));
                        const float m0 = __uint_as_float(sv.y);
                        mx = warp_max(m0);
                        const float w0 = ex2((m0 - mx) * LOG2E);
                        ll = w0 * __uint_as_float(sv.x);
                        const float l4 = __shfl_xor_sync(0xffffffffu, ll, 4);
#pragma unroll
                        for (int i = 0; i < 8; i++) wt[i] = __shfl_sync(0xffffffffu, w0, i);
                        ll += l4;
                        ll += __shfl_xor_sync(0xffffffffu, ll, 2);
                        if (!__any_sync(0xffffffffu, anyb & 1) || it >= SPIN_LIMIT) break;
                        uint32_t mask = 0;
#pragma unroll
                        for (int i = 0; i < 9; i++) mask |= (bad[i] & 1) << i;
                        const uint32_t pend = __reduce_or_sync(0xffffffffu, mask);
                        ld_rlx2x64_if(sv, sp, pend & 256);
#pragma unroll
                        for (int i = 0; i < 8; i++) ld_rlx2x64_if(v[i], rp + i * 128, pend & (1 << i));
                    }
                    ll += __shfl_xor_sync(0xffffffffu, ll, 1);
                    float4 acc = make_float4(0.f, 0.f, 0.f, 0.f), acd = acc;
#pragma unroll
                    for (int i = 0; i < 8; i += 2) {
                        acc.x += wt[i] * __uint_as_float(v[i].x); acc.y += wt[i] * __uint_as_float(v[i].y);
                        acc.z += wt[i] * __uint_as_float(v[i].z); acc.w += wt[i] * __uint_as_float(v[i].w);
                        acd.x += wt[i + 1] * __uint_as_float(v[i + 1].x); acd.y += wt[i + 1] * __uint_as_float(v[i + 1].y);
                        acd.z += wt[i + 1] * __uint_as_float(v[i + 1].z); acd.w += wt[i + 1] * __uint_as_float(v[i + 1].w);
                    }
                    acc.x += acd.x; acc.y += acd.y; acc.z += acd.z; acc.w += acd.w;
                    TL3(6, 0);
                    if (lane == 0) reinterpret_cast<float2*>(red + 1024)[x] = make_float2(mx, ll);
                    reinterpret_cast<float4*>(red)[tid] = acc;
                    const int d = kperm(16 * ((tid >> 2) & 3) + 8 * (tid & 1) + 64 * ((tid >> 1) & 1) + ((tid >> 4) & 7));
                    uint32_t od = sb + OFF_SS + 15 * 288 + 2 * d, ra = sb + OFF_SS + 8448;
                    asm volatile("" : "+r"(od), "+r"(ra));
                    bar_sync(2, 256);
                    if (x < 4) {
                        uint4 st[4];
                        float r[8];
#pragma unroll
                        for (int i = 0; i < 4; i++) st[i] = lds128(ra + 4096 + 16 * i);
#pragma unroll
                        for (int i = 0; i < 8; i++) r[i] = lds32(ra + 512 * i + 4 * tid);
                        float m2[4];
#pragma unroll
                        for (int i = 0; i < 4; i++) m2[i] = fmaxf(__uint_as_float(st[i].x), __uint_as_float(st[i].z));
                        const float mm = fmaxf(fmaxf(m2[0], m2[1]), fmaxf(m2[2], m2[3]));
                        float s0 = 0.f, s1 = 0.f, l0 = 0.f, l1 = 0.f;
#pragma unroll
                        for (int i = 0; i < 4; i++) {
                            const float f0 = ex2((__uint_as_float(st[i].x) - mm) * LOG2E), f1 = ex2((__uint_as_float(st[i].z) - mm) * LOG2E);
                            s0 += f0 * r[2 * i]; s1 += f1 * r[2 * i + 1];
                            l0 += f0 * __uint_as_float(st[i].y); l1 += f1 * __uint_as_float(st[i].w);
                        }
                        float inv;
                        asm("rcp.approx.ftz.f32 %0, %1;" : "=f"(inv) : "f"(l0 + l1));
                        const uint32_t ob = pack_bf16((s0 + s1) * inv, 0.f);
                        if (pass) asm volatile("st.shared.u16 [%0], %1;" :: "r"(od), "h"((uint16_t)ob) : "memory");
                        else st_rlx(&H.S->vec[1][h][j][d], (ob << 16) | tag);
                    }
                    __syncwarp();
                    if (pass && lane == 0) mbar_arrive(bar_vec + 8);
                    TL3(7, 0);
                    if (!pass) bar_sync(2, 256);
                }
            }
        }
    }
}

typedef CUresult (*EncodeFn)(CUtensorMap*, CUtensorMapDataType, cuuint32_t, void*, const cuuint64_t*, const cuuint64_t*,
                             const cuuint32_t*, const cuuint32_t*, CUtensorMapInterleave, CUtensorMapSwizzle,
                             CUtensorMapL2promotion, CUtensorMapFloatOOBfill);

void encode2d(EncodeFn fn, CUtensorMap* tm, void* ptr, uint64_t cols, uint64_t rows, uint32_t box_rows) {
    const cuuint64_t dims[2] = {cols, rows};
    const cuuint64_t strides[1] = {cols * 2};
    const cuuint32_t box[2] = {64, box_rows};
    const cuuint32_t es[2] = {1, 1};
    fn(tm, CU_TENSOR_MAP_DATA_TYPE_BFLOAT16, 2, ptr, dims, strides, box, es, CU_TENSOR_MAP_INTERLEAVE_NONE,
       CU_TENSOR_MAP_SWIZZLE_128B, CU_TENSOR_MAP_L2_PROMOTION_NONE, CU_TENSOR_MAP_FLOAT_OOB_FILL_NONE);
}

}

extern "C" void kernel_launch(void* const* d_in, const int* in_sizes, int n_in, void* d_out, int out_size) {
    (void)in_sizes; (void)n_in; (void)out_size;
    static EncodeFn encode = nullptr;
    static Scratch* scratch = nullptr;
    if (!encode) {
        cudaFuncSetAttribute(fused_decode_kernel, cudaFuncAttributeMaxDynamicSharedMemorySize, SMEM_BYTES + SMEM_EXTRA);
        void* fn = nullptr;
        cudaDriverEntryPointQueryResult qr;
        cudaGetDriverEntryPoint("cuTensorMapEncodeTiled", &fn, cudaEnableDefault, &qr);
        encode = (EncodeFn)fn;
        void* sp = nullptr;
        cudaGetSymbolAddress(&sp, g_scratch);
        scratch = (Scratch*)sp;
    }
    Params p;
    encode2d(encode, &p.tm_wq[0], d_in[9], 4096, 512, 128);
    encode2d(encode, &p.tm_wq[1], d_in[2], 4096, 512, 128);
    encode2d(encode, &p.tm_wuk,   d_in[3], 4096, 512, 128);
    encode2d(encode, &p.tm_wuv,   d_in[4], 4096, 512, 128);
    encode2d(encode, &p.tm_wo[1], d_in[10], 512, 4096, 128);
    encode2d(encode, &p.tm_wo[0], d_in[5], 512, 4096, 128);
    {
        const cuuint64_t dims[3] = {64, 16384, 8};
        const cuuint64_t strides[2] = {1024, 128};
        const cuuint32_t box[3] = {64, 16, 8};
        const cuuint32_t es[3] = {1, 1, 1};
        encode(&p.tm_ckv, CU_TENSOR_MAP_DATA_TYPE_BFLOAT16, 3, d_in[1], dims, strides, box, es, CU_TENSOR_MAP_INTERLEAVE_NONE,
               CU_TENSOR_MAP_SWIZZLE_128B, CU_TENSOR_MAP_L2_PROMOTION_NONE, CU_TENSOR_MAP_FLOAT_OOB_FILL_NONE);
    }
    p.wo[0] = (const __nv_bfloat16*)d_in[5];
    p.wo[1] = (const __nv_bfloat16*)d_in[10];
    p.out = (__nv_bfloat16*)d_out;
    Hot hp;
    hp.kp = (const char*)d_in[7];
    hp.vp = (const char*)d_in[8];
    hp.S = scratch;
    hp.x[0] = (const __nv_bfloat16*)d_in[6];
    hp.x[1] = (const __nv_bfloat16*)d_in[0];
    hp.zero = 0;
    hp.never = 0;
    cudaLaunchConfig_t cfg = {};
    cfg.gridDim = dim3(NCTA);
    cfg.blockDim = dim3(NTHREADS);
    cfg.dynamicSmemBytes = SMEM_BYTES + SMEM_EXTRA;
    cfg.stream = cudaStreamPerThread;
    cudaLaunchAttribute at[1];
    at[0].id = cudaLaunchAttributeCooperative;
    at[0].val.cooperative = 1;
    cfg.attrs = at;
    cfg.numAttrs = 1;
    cudaLaunchKernelEx(&cfg, fused_decode_kernel, hp, p);
}
```

```cpp
#include <cuda_runtime.h>
#include <cuda.h>
#include <cuda_bf16.h>
#include <stdint.h>

namespace {

constexpr int NCTA      = 128;
constexpr int NTHREADS  = 512;
constexpr int CH_BYTES  = 16384;
constexpr int NPIECE    = 128 * 64;
constexpr int RING      = 8;
#define PFV 12288
#define WIN 3
#define DL0 3250
#define DLS 1000
#define NB2 4650
#define NBS 1300
#define DLR 18
#define HS 31
#define XS 224
#define TG 5700
#define LAG 192
#define LAG2 96
#define LAG1 192
#define HURG 24
#define FSLEEP 600
#define QSLEEP 400
#define QD0 600
#define QD1 100
#define TRIG0 (20 * 128)
#define TRIG1 (32 * 128)
#define TRIG2 (50 * 128)
constexpr int SMEM_EXTRA = 0;
constexpr int A_SPLITS  = 8;
constexpr int A_TILES   = 4096 / A_SPLITS / 16;

constexpr int OFF_RING  = 0;
constexpr int OFF_XR    = OFF_RING + RING * CH_BYTES;
constexpr int OFF_SS    = OFF_XR + 4 * CH_BYTES;
constexpr int OFF_SP    = OFF_SS + 8 * 32 * 80;
constexpr int OFF_ALPHA = OFF_SP + 1024;
constexpr int OFF_OA    = OFF_ALPHA + 128;
constexpr int OFF_ST    = OFF_OA + 4 * 288;
constexpr int OFF_MLA   = OFF_ST + 64 * 32;
constexpr int OFF_QT    = OFF_MLA + 4 * A_SPLITS * 8;
constexpr int MG_BYTES  = 2048 + 128 + 32;
constexpr int OFF_MG    = OFF_QT + 4 * 256;
constexpr int OFF_META  = OFF_MG + 2 * MG_BYTES;
constexpr int OFF_EP    = OFF_META + 16;
constexpr int OFF_X     = OFF_SS + 4096;
constexpr int OFF_BAR   = OFF_EP + 16;
constexpr int NBAR      = 2 * RING + 8 + 2 + 3 + 4 + 3 + 1 + 8 + 8 + 2 + 2 + 2 + 1;
constexpr int I_INI     = 2 * RING + 8 + 2 + 3 + 4 + 3;
constexpr int SMEM_BYTES = OFF_BAR + NBAR * 8;

constexpr float LOG2E = 1.4426950408889634f;
constexpr float SCALE = 0.08838834764831845f;
constexpr uint32_t SPIN_LIMIT = 1u << 20;

struct Scratch {
    uint32_t ticket[2][64];
    uint32_t epoch[NCTA];
    uint32_t cntQ[64], cntA[64];
    float2   mlA[32][4][A_SPLITS];
    uint32_t vec[2][32][4][128];
    uint32_t q[2][4][4096];
    uint16_t qabs[4][8][2][4][2][32][8];
    float    pA[32][4][A_SPLITS][512];
    uint32_t pB[NPIECE][128];
    uint32_t mlB[NPIECE][8];
};
__device__ __align__(128) Scratch g_scratch;
#define TL(i) do {} while (0)
#define TL3(i, dep) do {} while (0)
#define TLG(i) do {} while (0)
#define TL2(i) do {} while (0)

struct Hot {
    const char *kp, *vp;
    Scratch* S;
    const __nv_bfloat16* x[2];
    uint32_t zero;
    uint32_t never;
};
struct Params {
    CUtensorMap tm_wq[2];
    CUtensorMap tm_wuk, tm_wuv;
    CUtensorMap tm_wo[2];
    CUtensorMap tm_ckv;
    const __nv_bfloat16* wo[2];
    __nv_bfloat16* out;
};

__device__ __forceinline__ void mbar_init(uint32_t bar, uint32_t cnt) {
    asm volatile("mbarrier.init.shared::cta.b64 [%0], %1;" :: "r"(bar), "r"(cnt) : "memory");
}
__device__ __forceinline__ void mbar_expect_tx(uint32_t bar, uint32_t bytes) {
    asm volatile("mbarrier.arrive.expect_tx.shared::cta.b64 _, [%0], %1;" :: "r"(bar), "r"(bytes) : "memory");
}
__device__ __forceinline__ void mbar_arrive(uint32_t bar) {
    asm volatile("mbarrier.arrive.shared::cta.b64 _, [%0];" :: "r"(bar) : "memory");
}
template <uint32_t LIMIT = SPIN_LIMIT>
__device__ __forceinline__ bool mbar_wait(uint32_t bar, uint32_t parity) {
    uint32_t done, it = 0;
    do {
        asm volatile("{\n.reg .pred p;\nmbarrier.try_wait.parity.shared::cta.b64 p, [%1], %2;\nselp.u32 %0, 1, 0, p;\n}"
                     : "=r"(done) : "r"(bar), "r"(parity) : "memory");
        if (++it > LIMIT) break;
    } while (!done);
    return done;
}
__device__ __forceinline__ void bulk_load(uint32_t dst, const void* src, uint32_t bytes, uint32_t bar, uint64_t pol) {
    asm volatile("cp.async.bulk.shared::cluster.global.mbarrier::complete_tx::bytes.L2::cache_hint [%0], [%1], %2, [%3], %4;"
                 :: "r"(dst), "l"(src), "r"(bytes), "r"(bar), "l"(pol) : "memory");
}
__device__ __forceinline__ uint64_t policy_evict_first() {
    uint64_t pol;
    asm volatile("createpolicy.fractional.L2::evict_first.b64 %0, 1.0;" : "=l"(pol));
    return pol;
}
__device__ __forceinline__ void bar_sync(int id, int n)   { asm volatile("bar.sync %0, %1;" :: "r"(id), "r"(n) : "memory"); }
__device__ __forceinline__ void bar_arrive(int id, int n) { asm volatile("bar.arrive %0, %1;" :: "r"(id), "r"(n) : "memory"); }
__device__ __forceinline__ void ldsm4(uint32_t (&r)[4], uint32_t addr) {
    asm volatile("ldmatrix.sync.aligned.m8n8.x4.shared.b16 {%0,%1,%2,%3}, [%4];"
                 : "=r"(r[0]), "=r"(r[1]), "=r"(r[2]), "=r"(r[3]) : "r"(addr) : "memory");
}
__device__ __forceinline__ void ldsm4t(uint32_t (&r)[4], uint32_t addr) {
    asm volatile("ldmatrix.sync.aligned.m8n8.x4.trans.shared.b16 {%0,%1,%2,%3}, [%4];"
                 : "=r"(r[0]), "=r"(r[1]), "=r"(r[2]), "=r"(r[3]) : "r"(addr) : "memory");
}
__device__ __forceinline__ void mma(float (&c)[4], uint32_t a0, uint32_t a1, uint32_t a2, uint32_t a3, uint32_t b0, uint32_t b1) {
    asm volatile("mma.sync.aligned.m16n8k16.row.col.f32.bf16.bf16.f32 {%0,%1,%2,%3}, {%4,%5,%6,%7}, {%8,%9}, {%0,%1,%2,%3};"
                 : "+f"(c[0]), "+f"(c[1]), "+f"(c[2]), "+f"(c[3])
                 : "r"(a0), "r"(a1), "r"(a2), "r"(a3), "r"(b0), "r"(b1));
}
__device__ __forceinline__ uint32_t prmt(uint32_t a, uint32_t b, uint32_t s) {
    uint32_t r; asm("prmt.b32 %0, %1, %2, %3;" : "=r"(r) : "r"(a), "r"(b), "r"(s)); return r;
}
__device__ __forceinline__ uint32_t pack_bf16(float lo, float hi) {
    uint32_t r; asm("cvt.rn.bf16x2.f32 %0, %1, %2;" : "=r"(r) : "f"(hi), "f"(lo)); return r;
}
__device__ __forceinline__ float bf16_round(float v) { return __uint_as_float(pack_bf16(0.f, v) & 0xffff0000u); }
__device__ __forceinline__ float ex2(float x) { float r; asm("ex2.approx.ftz.f32 %0, %1;" : "=f"(r) : "f"(x)); return r; }
__device__ __forceinline__ uint4 ld_rlx4(const void* p) {
    uint4 v;
    asm volatile("ld.relaxed.gpu.global.v4.u32 {%0,%1,%2,%3}, [%4];" : "=r"(v.x), "=r"(v.y), "=r"(v.z), "=r"(v.w) : "l"(p) : "memory");
    return v;
}
__device__ __forceinline__ uint32_t ld_acq(const void* p) {
    uint32_t v; asm volatile("ld.acquire.gpu.global.u32 %0, [%1];" : "=r"(v) : "l"(p) : "memory"); return v;
}
__device__ __forceinline__ void st_rlx(void* p, uint32_t v) { asm volatile("st.relaxed.gpu.global.u32 [%0], %1;" :: "l"(p), "r"(v) : "memory"); }
__device__ __forceinline__ void st_rlx4(void* p, uint32_t a, uint32_t b, uint32_t c, uint32_t d) {
    asm volatile("st.relaxed.gpu.global.v4.u32 [%0], {%1,%2,%3,%4};" :: "l"(p), "r"(a), "r"(b), "r"(c), "r"(d) : "memory");
}
__device__ __forceinline__ float warp_max(float v) {
    int k = __float_as_int(v);
    k ^= (k >> 31) & 0x7fffffff;
    k = __reduce_max_sync(0xffffffffu, k);
    k ^= (k >> 31) & 0x7fffffff;
    return __int_as_float(k);
}
__device__ __forceinline__ uint32_t tagf(float v, uint32_t par) { return (__float_as_uint(v) & ~1u) | par; }
__device__ __forceinline__ void wait_count(const uint32_t* c, uint32_t val, uint32_t sleep) {
#pragma unroll 1
    for (uint32_t it = 0; it < SPIN_LIMIT && ld_acq(c) != val; it++) __nanosleep(sleep);
}
__device__ __forceinline__ uint32_t take_ticket(uint32_t* c) {
    uint32_t v; asm volatile("atom.relaxed.gpu.global.add.u32 %0, [%1], 1;" : "=r"(v) : "l"(c) : "memory"); return v;
}
__device__ __forceinline__ void add_rel(uint32_t* c) { asm volatile("red.release.gpu.global.add.u32 [%0], 1;" :: "l"(c) : "memory"); }
__device__ __forceinline__ uint32_t tag16(uint32_t ep) { return (ep & 0x7fffu) | 0x8000u; }
__device__ __forceinline__ void gather128(const uint32_t* src, uint32_t tag, unsigned char* dst, int lane, uint32_t sleep) {
    uint4 v;
#pragma unroll 1
    for (uint32_t it = 0; it < SPIN_LIMIT; it++) {
        v = ld_rlx4(src + lane * 4);
        const bool ok = ((((v.x ^ tag) | (v.y ^ tag)) | ((v.z ^ tag) | (v.w ^ tag))) & 0xffffu) == 0;
        if (__all_sync(0xffffffffu, ok)) break;
        __nanosleep(sleep);
    }
    *reinterpret_cast<uint2*>(dst + lane * 8) = make_uint2(prmt(v.x, v.y, 0x7632), prmt(v.z, v.w, 0x7632));
}

__device__ __forceinline__ void bulk_load_nh(uint32_t dst, const void* src, uint32_t bytes, uint32_t bar) {
    asm volatile("cp.async.bulk.shared::cluster.global.mbarrier::complete_tx::bytes [%0], [%1], %2, [%3];"
                 :: "r"(dst), "l"(src), "r"(bytes), "r"(bar) : "memory");
}
__device__ __forceinline__ void tma2d_hint(uint32_t dst, const CUtensorMap* tm, int c0, int c1, uint32_t bar, uint64_t pol) {
    asm volatile("cp.async.bulk.tensor.2d.shared::cluster.global.mbarrier::complete_tx::bytes.L2::cache_hint [%0], [%1, {%3, %4}], [%2], %5;"
                 :: "r"(dst), "l"(tm), "r"(bar), "r"(c0), "r"(c1), "l"(pol) : "memory");
}
__device__ __forceinline__ void tma3d_hint(uint32_t dst, const CUtensorMap* tm, int c0, int c1, int c2, uint32_t bar, uint64_t pol) {
    asm volatile("cp.async.bulk.tensor.3d.shared::cluster.global.mbarrier::complete_tx::bytes.L2::cache_hint [%0], [%1, {%3, %4, %5}], [%2], %6;"
                 :: "r"(dst), "l"(tm), "r"(bar), "r"(c0), "r"(c1), "r"(c2), "l"(pol) : "memory");
}
__device__ __forceinline__ void prefetch32(const void* p) { asm volatile("cp.async.bulk.prefetch.L2.global [%0], 32;" :: "l"(p) : "memory"); }
__device__ __forceinline__ void prefetch_tm(const CUtensorMap* tm) { asm volatile("prefetch.tensormap [%0];" :: "l"(tm) : "memory"); }
__device__ __forceinline__ int kperm(int d) { return (d & ~15) | ((d & 6) << 1) | ((d >> 2) & 2) | (d & 1); }

template <int NK>
__device__ __forceinline__ uint32_t load_wT(uint32_t (&w)[NK][4][4], uint32_t base, int lane) {
    const int r8 = lane & 7;
    const uint32_t a0 = base + (r8 + 8 * (lane >> 4)) * 128 + ((((lane >> 3) & 1) ^ r8) << 4);
    uint32_t dep = 0;
#pragma unroll
    for (int s = 0; s < NK; s++)
#pragma unroll
        for (int mt = 0; mt < 4; mt++) { ldsm4t(w[s][mt], (a0 ^ (mt << 5)) + s * 2048); dep |= w[s][mt][0]; }
    return dep;
}

__device__ __forceinline__ bool mbar_test(uint32_t bar, uint32_t parity) {
    uint32_t done;
    asm volatile("{\n.reg .pred p;\nmbarrier.test_wait.parity.shared::cta.b64 p, [%1], %2;\nselp.u32 %0, 1, 0, p;\n}"
                 : "=r"(done) : "r"(bar), "r"(parity) : "memory");
    return done;
}
__device__ __forceinline__ void st_rlx2x64(void* p, uint32_t a, uint32_t b, uint32_t c, uint32_t d) {
    asm volatile("{\n.reg .b64 u, v;\nmov.b64 u, {%1,%2};\nmov.b64 v, {%3,%4};\nst.relaxed.gpu.global.v2.b64 [%0], {u, v};\n}"
                 :: "l"(p), "r"(a), "r"(b), "r"(c), "r"(d) : "memory");
}
__device__ __forceinline__ void ld_rlx2x64_if(uint4& v, const void* p, uint32_t pred) {
    asm volatile("{\n.reg .pred p;\n.reg .b64 u, v;\nsetp.ne.u32 p, %5, 0;\nmov.b64 u, {%0,%1};\nmov.b64 v, {%2,%3};\n"
                 "@p ld.relaxed.gpu.global.v2.b64 {u, v}, [%4];\nmov.b64 {%0,%1}, u;\nmov.b64 {%2,%3}, v;\n}"
                 : "+r"(v.x), "+r"(v.y), "+r"(v.z), "+r"(v.w) : "l"(p), "r"(pred) : "memory");
}
__device__ __forceinline__ uint4 lds128(uint32_t a) {
    uint4 v; asm volatile("ld.shared.v4.u32 {%0,%1,%2,%3}, [%4];" : "=r"(v.x), "=r"(v.y), "=r"(v.z), "=r"(v.w) : "r"(a) : "memory"); return v;
}
__device__ __forceinline__ float lds32(uint32_t a) { float v; asm volatile("ld.shared.f32 %0, [%1];" : "=f"(v) : "r"(a) : "memory"); return v; }
__device__ __forceinline__ uint32_t untagged(const uint4& v, uint32_t par) {
    uint32_t bad;
    asm("lop3.b32 %0, %1, %2, %3, 0x7e;" : "=r"(bad) : "r"(v.x), "r"(v.z), "r"(par));
    return bad;
}
__device__ __forceinline__ uint32_t or3(uint32_t a, uint32_t b, uint32_t c) {
    uint32_t r; asm("lop3.b32 %0, %1, %2, %3, 0xfe;" : "=r"(r) : "r"(a), "r"(b), "r"(c)); return r;
}
__device__ __forceinline__ void red_bf2(void* p, uint32_t v) {
    asm volatile("red.relaxed.gpu.global.add.noftz.bf16x2 [%0], %1;" :: "l"(p), "r"(v) : "memory");
}

__global__ void __launch_bounds__(NTHREADS, 1) fused_decode_kernel(const __grid_constant__ Hot H, const __grid_constant__ Params P) {
    asm volatile("{\n.reg .pred p;\nsetp.eq.u32 p, %2, 0;\n@p cp.async.bulk.prefetch.L2.global [%0], %1;\n}"
                 :: "l"(H.vp + (size_t)blockIdx.x * CH_BYTES), "n"(PFV), "r"(threadIdx.x) : "memory");
    if (H.never) return;
    const uint64_t pol = policy_evict_first();
    extern __shared__ __align__(1024) unsigned char smem[];
    const uint32_t sb = (uint32_t)__cvta_generic_to_shared(smem);
    const int bid = blockIdx.x, h = bid >> 2, j = bid & 3;
    const int lane = threadIdx.x & 31;
    const int g = lane >> 2, t = lane & 3;
    const uint32_t bar_full = sb + OFF_BAR, bar_empty = bar_full + RING * 8;
    const uint32_t bar_xfull = bar_empty + RING * 8, bar_xempty = bar_xfull + 32, bar_vec = bar_xempty + 32, bar_trig = bar_vec + 16;
    const uint32_t bar_wo = bar_trig + 24, bar_cmb = bar_wo + 32, bar_ini = bar_cmb + 24, bar_gat = bar_ini + 8, bar_qreq = bar_gat + 64, bar_qfull = bar_qreq + 32;
    const uint32_t bar_mempty = bar_qfull + 32, bar_mfull = bar_mempty + 16;
    const uint32_t bar_sfull = bar_mfull + 16, bar_xdone = bar_sfull + 16;
    const int mat = bid & 1, cb = bid >> 1;
    const int ab = h & 3, asplit = h >> 2;
    const int br = j < 2, hp = h & 7, cbk = 2 * (h >> 3) + (j & 1);
    const int hl = br ? 24 + hp : 0;

    const char* kp = H.kp;
    const char* vp = H.vp;
    if (threadIdx.x == 0) {
        mbar_init(bar_full, 1);
        asm volatile("fence.mbarrier_init.release.cluster;" ::: "memory");
        mbar_expect_tx(bar_full, CH_BYTES);
        bulk_load(sb + OFF_RING, kp + bid * CH_BYTES, CH_BYTES, bar_full, pol);
        TL(0); TLG(0);
#pragma unroll
        for (int i = 0; i < 4; i++) mbar_init(bar_xfull + i * 8, 1);
        mbar_init(bar_full + 8, 1);
        mbar_init(bar_ini, 1);
        asm volatile("fence.mbarrier_init.release.cluster;" ::: "memory");
#pragma unroll
        for (int i = 0; i < 4; i++) {
            mbar_expect_tx(bar_xfull + i * 8, CH_BYTES);
            tma2d_hint(sb + OFF_XR + i * CH_BYTES, &P.tm_wq[mat], 64 * cb, 128 * i, bar_xfull + i * 8, pol);
            if (i == 0) {
                mbar_expect_tx(bar_ini, 4096 + 16);
                bulk_load_nh(sb + OFF_EP, &H.S->epoch[4 * h], 16, bar_ini);
                bulk_load_nh(sb + OFF_X, H.x[mat], 4096, bar_ini);
            }
        }
        mbar_expect_tx(bar_full + 8, CH_BYTES);
        bulk_load(sb + OFF_RING + CH_BYTES, vp + bid * CH_BYTES, CH_BYTES, bar_full + 8, pol);
        *reinterpret_cast<int*>(smem + OFF_META) = bid;
#pragma unroll
        for (int i = 2; i < NBAR; i++)
            if ((i < 2 * RING || i >= 2 * RING + 4) && i != I_INI)
                mbar_init(bar_full + i * 8, ((i >= RING && i < 2 * RING) || (i >= NBAR - 5 && i < NBAR - 1)) ? 4
                                          : (i >= 2 * RING + 4 && i < 2 * RING + 10) ? 8 : i == NBAR - 1 ? 9 : 1);
        asm volatile("fence.mbarrier_init.release.cluster;" ::: "memory");
        mbar_arrive(bar_qreq);
    }

    __syncwarp();
    const int warp = __shfl_sync(0xffffffffu, threadIdx.x >> 5, 0);
    auto epoch = [&]() -> uint32_t {
        mbar_wait(bar_ini, 0);
        return __shfl_sync(0xffffffffu, reinterpret_cast<const uint32_t*>(smem + OFF_EP)[j], 0) + 1;
    };

    if (warp >= 12) {
        asm volatile("setmaxnreg.dec.sync.aligned.u32 40;");
        bar_sync(1, 512);
        const uint32_t ep = epoch();
        if (warp == 12) {
            if (lane == 0) {
                uint32_t* tick = &H.S->ticket[ep & 1][threadIdx.x & H.zero];
                if (bid == 0) H.S->ticket[(ep & 1) ^ 1][0] = 0;
                int ntrig = 0, piece = bid, i = 2;
                uint32_t next = 0, tclaim = clock(), tg = 0;
#pragma unroll 1
                for (;; i++) {
                    const int s = i % RING;
                    if (i <= 4) mbar_wait<2048>(bar_xfull + (i - 2) * 8, 0);
                    if (i >= WIN) {
                        mbar_wait(bar_full + ((i - WIN) % RING) * 8, ((i - WIN) / RING) & 1);
                        if (i - WIN < 192) TL2(i - WIN);
                    }
                    if (i >= RING && !mbar_wait(bar_empty + s * 8, ((i / RING) - 1) & 1)) break;
                    if (!(i & 1)) {
                        piece = i == 2 ? NCTA + bid : 2 * NCTA + (int)next;
                        reinterpret_cast<volatile int*>(smem + OFF_META)[s >> 1] = piece < NPIECE ? piece : -1;
                        mbar_arrive(bar_qreq + (s >> 1) * 8);
                        while (ntrig < 3 && piece >= (ntrig == 0 ? TRIG0 : ntrig == 1 ? TRIG1 : TRIG2)) mbar_arrive(bar_trig + 8 * ntrig++);
                        if (piece >= NPIECE) break;
                        tg = tclaim + (NPIECE - piece) * DLR;
                    }
                    mbar_expect_tx(bar_full + s * 8, CH_BYTES);
                    bulk_load(sb + OFF_RING + s * CH_BYTES, ((i & 1) ? vp : kp) + (size_t)piece * CH_BYTES, CH_BYTES, bar_full + s * 8, pol);
                    if ((piece & 127) == 0 && piece + 2 * NCTA < NPIECE) prefetch32(((i & 1) ? vp : kp) + (size_t)(piece + 2 * NCTA) * CH_BYTES);
                    if ((piece >> 7) == 60) prefetch32(P.wo[br] + (hp + 16 * (i & 1)) * 65536 + 64 * cbk);
                    if (i & 1) {
                        if (hl >= HS && piece >= NPIECE - XS) next = NPIECE - 2 * NCTA;
                        else { next = take_ticket(tick); tclaim = clock(); }
                    }
                }
                mbar_wait(bar_xdone, 0);
                if (i >= RING) mbar_wait(bar_empty + (i % RING) * 8 + 8, ((i / RING) - 1) & 1);
                const int tlook = TG - (31 - hl) * 64 * DLR;
                bool look = hl >= HS;
                auto since = [&]() -> int {
                    const int now = (int)((uint32_t)clock() - tg);
                    if (look && now >= tlook) { mbar_arrive(bar_cmb + 16); look = false; }
                    return now;
                };
#pragma unroll 1
                for (int k = 0; k < 4; k++) {
                    const uint32_t dst = sb + (k < 2 ? OFF_RING + (i % RING) * CH_BYTES : OFF_XR) + k * CH_BYTES;
                    const int wi = k - 2;
                    const uint32_t wb = wi >= 0 ? bar_wo + wi * 8 : bar_full + ((i + wi) % RING) * 8, wp = wi >= 0 ? 0 : ((i + wi) / RING) & 1;
                    while (wi >= 0 && hl < HS && since() < NB2 + wi * NBS) {}
                    while (!mbar_test(wb, wp) && since() < DL0 + k * DLS) {}
                    mbar_expect_tx(bar_wo + k * 8, CH_BYTES);
                    tma2d_hint(dst, &P.tm_wo[br], 64 * cbk, (hp + 8 * k) * 128, bar_wo + k * 8, pol);
                }
                while (look) since();
                TL(1);
            }
        } else if (warp == 15) {
            const uint32_t par = ep & 1;
            const uint32_t t0 = 64 * (32 * j + h + 1) + LAG, t1 = 64 * (96 + (hl < HURG ? hl : hl - 8) + 1) + LAG + LAG1, t2 = 64 * (96 + hl + 1) + LAG2;
            uint32_t fired = 0;
#pragma unroll 1
            for (int r = 0;; r++) {
                const unsigned char* mg = smem + OFF_MG + (r & 1) * MG_BYTES;
                if (!mbar_wait(bar_sfull + (r & 1) * 8, (r >> 1) & 1)) break;
                const uint32_t piece = *reinterpret_cast<const uint32_t*>(mg + 2048 + 144);
                if (piece < NPIECE) {
                    const float4 mw = *reinterpret_cast<const float4*>(mg + 2048 + 128);
                    const float mm = fmaxf(fmaxf(mw.x, mw.y), fmaxf(mw.z, mw.w));
                    const float e0 = ex2((mw.x - mm) * LOG2E), e1 = ex2((mw.y - mm) * LOG2E);
                    const float e2 = ex2((mw.z - mm) * LOG2E), e3 = ex2((mw.w - mm) * LOG2E);
                    float l = reinterpret_cast<const float*>(mg + 2048)[lane] * ((lane & 16) ? ((lane & 8) ? e3 : e2) : ((lane & 8) ? e1 : e0));
#pragma unroll
                    for (int o = 16; o > 0; o >>= 1) l += __shfl_xor_sync(0xffffffffu, l, o);
                    uint32_t* dst = &H.S->pB[piece][lane * 4];
                    if (piece >= NPIECE - 256) mbar_wait(bar_xdone, 0);
                    if (lane < 2) st_rlx2x64(&H.S->mlB[piece][lane * 4], tagf(l, par), __float_as_uint(mm), par, 0);
                    mbar_wait(bar_mfull + (r & 1) * 8, (r >> 1) & 1);
                    const float4 a = reinterpret_cast<const float4*>(mg)[lane],      b = reinterpret_cast<const float4*>(mg)[32 + lane];
                    const float4 c = reinterpret_cast<const float4*>(mg)[64 + lane], d = reinterpret_cast<const float4*>(mg)[96 + lane];
                    st_rlx2x64(dst, tagf((a.x * e0 + b.x * e1) + (c.x * e2 + d.x * e3), par), __float_as_uint((a.y * e0 + b.y * e1) + (c.y * e2 + d.y * e3)),
                                    tagf((a.z * e0 + b.z * e1) + (c.z * e2 + d.z * e3), par), __float_as_uint((a.w * e0 + b.w * e1) + (c.w * e2 + d.w * e3)));
                    TL3(3, 0);
                }
                __syncwarp();
                const uint32_t now = (piece >= t0 ? 1u : 0u) | (piece >= t1 ? 2u : 0u) | (piece >= t2 && hl < HS ? 4u : 0u);
                if (lane < 3 && ((now & ~fired) >> lane & 1)) mbar_arrive(bar_cmb + lane * 8);
                fired = now;
                if (piece >= NPIECE) break;
                if (lane == 0) mbar_arrive(bar_mempty + (r & 1) * 8);
            }
        } else if (warp == 14) {
            mbar_wait<2048>(bar_xfull + 24, 0);
            __nanosleep(QD0);
#pragma unroll 1
            for (int r = 0;; r++) {
                if (!mbar_wait(bar_qreq + (r & 3) * 8, (r >> 2) & 1)) break;
                const int piece = reinterpret_cast<volatile int*>(smem + OFF_META)[r & 3];
                if (piece >= 0) gather128(&H.S->q[0][piece >> 11][((piece >> 6) & 31) * 128], tag16(ep), smem + OFF_QT + (r & 3) * 256, lane, QD1);
                __syncwarp();
                if (lane == 0) mbar_arrive(bar_qfull + (r & 3) * 8);
                if (piece < 0) break;
            }
        } else if (warp == 13) {
            if (lane == 0) { prefetch_tm(&P.tm_wuk); prefetch_tm(j == 0 ? &P.tm_ckv : &P.tm_wuv); }
            int n = 4;
            auto acquire = [&](uint32_t bytes) -> uint32_t {
                mbar_wait(bar_xempty + (n & 3) * 8, ((n >> 2) - 1) & 1);
                mbar_expect_tx(bar_xfull + (n & 3) * 8, bytes);
                return (uint32_t)(n++ & 3);
            };
            if (lane == 0) {
#pragma unroll 1
                for (int k = 0; k < 2; k++) {
                    const uint32_t s = acquire(CH_BYTES);
                    tma2d_hint(sb + OFF_XR + s * CH_BYTES, &P.tm_wuk, h * 128 + 64 * k, 128 * j, bar_xfull + s * 8, pol);
                }
                if (j >= 2) {
                    mbar_wait(bar_trig, 0);
#pragma unroll 1
                    for (int k = 0; k < 4; k++) {
                        const uint32_t s = acquire(CH_BYTES);
                        tma2d_hint(sb + OFF_XR + s * CH_BYTES, &P.tm_wuv, h * 128 + 64 * (j - 2), 128 * k, bar_xfull + s * 8, pol);
                    }
                }
            }
            __syncwarp();
            if (j == 0) bar_sync(10, 64);
            if (lane == 0) {
                if (j == 0) wait_count(H.S->cntQ, ep * NCTA, QSLEEP);
                else if (j >= 2) { mbar_wait(bar_trig + 8, 0); wait_count(H.S->cntA, ep * 4 * A_SPLITS, FSLEEP); }
                asm volatile("fence.proxy.async.global;" ::: "memory");
                if (j == 0) {
#pragma unroll 1
                    for (int k = 0; k < 4; k++) {
                        const uint32_t s = acquire(CH_BYTES);
                        bulk_load_nh(sb + OFF_XR + s * CH_BYTES, &H.S->qabs[ab][2 * k][0][0][0][0][0], CH_BYTES, bar_xfull + s * 8);
                    }
#pragma unroll 1
                    for (int k = 0; k < A_TILES; k++) {
                        const uint32_t s = acquire(CH_BYTES);
                        tma3d_hint(sb + OFF_XR + s * CH_BYTES, &P.tm_ckv, 0, ab * 4096 + 16 * (k * A_SPLITS + asplit), 0, bar_xfull + s * 8, pol);
                    }
                } else if (j >= 2) {
#pragma unroll 1
                    for (int k = 0; k < 4; k++) {
                        const uint32_t s = acquire(CH_BYTES + A_SPLITS * 8);
                        bulk_load_nh(sb + OFF_XR + s * CH_BYTES, &H.S->pA[h][k][0][0], CH_BYTES, bar_xfull + s * 8);
                        bulk_load_nh(sb + OFF_MLA + k * A_SPLITS * 8, &H.S->mlA[h][k][0], A_SPLITS * 8, bar_xfull + s * 8);
                    }
                }
            }
            __syncwarp();
            mbar_wait(bar_trig + 16, 0);
            if (lane == 0) {
                prefetch_tm(&P.tm_wo[br]);
                wait_count(H.S->cntQ, ep * NCTA, QSLEEP);
                mbar_arrive(bar_xdone);
            }
        }
    } else if (warp < 4) {
        asm volatile("setmaxnreg.dec.sync.aligned.u32 88;");
        bar_sync(1, 512);
        const uint32_t ep = epoch();
        const bool valid = (t == (g >> 1));
        const bool odd = g & 1;
        const int r8 = lane & 7;
        const uint32_t koff = (warp * 16 + r8 + 8 * ((lane >> 3) & 1)) * 256 + (((lane >> 4) ^ r8) << 4);
        const uint32_t voff = (warp * 16 + r8 + 8 * (lane >> 4)) * 256 + ((((lane >> 3) & 1) ^ r8) << 4);
        int r = 0;
#pragma unroll 1
        for (;; r++) {
            const int sk = (2 * r) % RING, sv = sk + 1;
            const uint32_t ph = ((2 * r) / RING) & 1;
            unsigned char* mg = smem + OFF_MG + (r & 1) * MG_BYTES;
            if (!mbar_wait(bar_qfull + (r & 3) * 8, ph)) break;
            if (r == 0 && threadIdx.x == 0) TL(4);
            const int piece = reinterpret_cast<volatile int*>(smem + OFF_META)[r & 3];
            if (piece < 0) {
                mbar_wait(bar_mempty + (r & 1) * 8, ((r >> 1) - 1) & 1);
                if (lane == 0) { *reinterpret_cast<int*>(mg + 2048 + 144) = piece; mbar_arrive(bar_sfull + (r & 1) * 8); }
                break;
            }
            uint32_t qf[16];
#pragma unroll
            for (int u = 0; u < 16; u++) qf[u] = reinterpret_cast<const uint32_t*>(smem + OFF_QT + (r & 3) * 256)[4 * (u ^ g) + t];
            mbar_wait(bar_full + sk * 8, ph);
            const uint32_t ka = sb + OFF_RING + sk * CH_BYTES + koff;
            float c0[4] = {0.f, 0.f, 0.f, 0.f}, c1[4] = {0.f, 0.f, 0.f, 0.f};
#pragma unroll
            for (int s = 0; s < 8; s += 2) {
                uint32_t a[4], b[4];
                ldsm4(a, ka ^ (s << 5));
                ldsm4(b, ka ^ ((s + 1) << 5));
                mma(c0, a[0], a[1], a[2], a[3], qf[2 * s], qf[2 * s + 1]);
                mma(c1, b[0], b[1], b[2], b[3], qf[2 * s + 2], qf[2 * s + 3]);
            }
            float slo = odd ? c0[1] + c1[1] : c0[0] + c1[0];
            float shi = odd ? c0[3] + c1[3] : c0[2] + c1[2];
            if (lane == 0) mbar_arrive(bar_empty + sk * 8 + (__float_as_uint(slo) & H.zero));
            slo = bf16_round(bf16_round(slo) * SCALE);
            shi = bf16_round(bf16_round(shi) * SCALE);
            const float m = warp_max(valid ? fmaxf(slo, shi) : -INFINITY);
            const float plo = valid ? ex2((slo - m) * LOG2E) : 0.f;
            const float phi = valid ? ex2((shi - m) * LOG2E) : 0.f;
            if (r >= 2) mbar_wait(bar_mempty + (r & 1) * 8, ((r >> 1) - 1) & 1);
            if (valid) reinterpret_cast<float*>(mg + 2048)[warp * 8 + g] = plo + phi;
            if (lane == 0) { reinterpret_cast<float*>(mg + 2048 + 128)[warp] = m; *reinterpret_cast<int*>(mg + 2048 + 144) = piece; }
            __syncwarp();
            if (lane == 0) mbar_arrive(bar_sfull + (r & 1) * 8);
            const uint32_t b0 = odd ? pack_bf16(0.f, plo) : pack_bf16(plo, 0.f);
            const uint32_t b1 = odd ? pack_bf16(0.f, phi) : pack_bf16(phi, 0.f);
            mbar_wait(bar_full + sv * 8, ph);
            if (warp == 0) TL3(0, 0);
            const uint32_t va = sb + OFF_RING + sv * CH_BYTES + voff;
            float ev[8], od[8];
#pragma unroll
            for (int i = 0; i < 8; i++) {
                uint32_t a[4];
                float acc[4] = {0.f, 0.f, 0.f, 0.f};
                ldsm4t(a, va ^ (i << 5));
                mma(acc, a[0], a[1], a[2], a[3], b0, b1);
                ev[i] = acc[0] + acc[3]; od[i] = acc[1] + acc[2];
            }
#pragma unroll
            for (int i = 0; i < 8; i += 2) {
                ev[i] += __shfl_xor_sync(0xffffffffu, ev[i + 1], 1);
                od[i] += __shfl_xor_sync(0xffffffffu, od[i + 1], 1);
            }
#pragma unroll
            for (int i = 0; i < 8; i += 4) {
                ev[i] += __shfl_xor_sync(0xffffffffu, ev[i + 2], 2);
                od[i] += __shfl_xor_sync(0xffffffffu, od[i + 2], 2);
            }
            reinterpret_cast<float4*>(mg)[warp * 32 + lane] = make_float4(ev[0], od[0], ev[4], od[4]);
            __syncwarp();
            if (lane == 0) {
                mbar_arrive(bar_mfull + (r & 1) * 8);
                mbar_arrive(bar_empty + sv * 8 + ((__float_as_uint(ev[0]) | __float_as_uint(ev[4])) & H.zero));
            }
        }
        TL3(2, 0);
        {
            int lane2 = lane;
            asm volatile("" : "+r"(lane2));
            const int g2 = lane2 >> 2;
            uint16_t* outp = reinterpret_cast<uint16_t*>(P.out) + (lane2 & 3) * 1024 + 512 * br + 64 * cbk + 16 * warp + ((g2 & 1) ? g2 + 7 : g2);
            const uint32_t sel = (g2 & 1) ? 0x3276 : 0x5410;
            const uint32_t aoff = (r8 + 8 * (lane2 >> 4)) * 128 + (((2 * warp + ((lane2 >> 3) & 1)) ^ r8) << 4);
            uint32_t a0 = sb + OFF_RING + ((2 * r) % RING) * CH_BYTES + aoff;
            uint32_t vp0 = sb + OFF_SS + (g2 >> 1) * 288 + 8 * (lane2 & 3);
            float d[4][4];
#pragma unroll
            for (int u = 0; u < 4; u++) d[u][0] = d[u][1] = d[u][2] = d[u][3] = 0.f;
            uint2 ob[8];
            auto load_v = [&]() {
#pragma unroll
                for (int s = 0; s < 8; s++)
                    asm volatile("ld.shared.v2.u32 {%0,%1}, [%2];" : "=r"(ob[s].x), "=r"(ob[s].y) : "r"(vp0 + 32 * s) : "memory");
            };
            uint32_t wf[8][4];
            auto load_w = [&]() {
#pragma unroll
                for (int s = 0; s < 8; s++) ldsm4t(wf[s], a0 + s * 2048);
            };
            auto mmas = [&]() {
#pragma unroll
                for (int s = 0; s < 8; s++) mma(d[s & 3], wf[s][0], wf[s][1], wf[s][2], wf[s][3], ob[s].x, ob[s].y);
            };
            int k = 0;
#pragma unroll 1
            for (;;) {
                mbar_wait(bar_wo + k * 8, 0);
                load_w();
                mbar_wait(bar_vec + (k ? 8 : 0), 0);
                load_v();
                mmas();
                if (k) break;
                a0 += CH_BYTES;
                vp0 += 4 * 288;
#pragma unroll 1
                for (k = 1;;) {
                    load_v();
                    uint32_t dep = 0;
#pragma unroll
                    for (int s = 0; s < 8; s++) dep |= ob[s].x;
                    a0 += dep & H.zero;
                    mbar_wait(bar_wo + k * 8, 0);
                    load_w();
                    mmas();
                    if (k == 3) goto done;
                    const bool have = k == 1 || mbar_test(bar_vec + 8, 0);
                    a0 = k == 1 ? sb + OFF_XR + 2 * CH_BYTES + aoff : a0 + CH_BYTES;
                    vp0 += 4 * 288;
                    k++;
                    if (!have) break;
                }
            }
        done:
            const uint32_t e = pack_bf16((d[0][0] + d[1][0]) + (d[2][0] + d[3][0]), (d[0][2] + d[1][2]) + (d[2][2] + d[3][2]));
            red_bf2(outp, prmt(e, __shfl_xor_sync(0xffffffffu, e, 4), sel));
            TL3(12, 0);
        }
    } else {
        asm volatile("setmaxnreg.inc.sync.aligned.u32 192;");
        const int x = warp - 4, tid = threadIdx.x - 128;
        bar_sync(1, 512);
        const uint32_t ep = epoch();
        const uint32_t tag = tag16(ep), par = ep & 1;
        uint32_t* qdst = &H.S->q[mat][tid >> 6][mat ? kperm(64 * cb + (tid & 63)) : 64 * cb + (tid & 63)];
        if (tid < 16) reinterpret_cast<uint32_t*>(P.out)[bid * 16 + tid] = 0u;
        if (!mat && cb >= 32) {
            st_rlx4(&H.S->pB[NPIECE - 512 + 8 * cb + x][lane * 4], par ^ 1, par ^ 1, par ^ 1, par ^ 1);
            if (lane < 2) st_rlx4(&H.S->mlB[NPIECE - 512 + 8 * cb + x][lane * 4], par ^ 1, par ^ 1, par ^ 1, par ^ 1);
        }
        const uint32_t xr = sb + OFF_XR;
        auto xwait = [&](int n) { mbar_wait(bar_xfull + (n & 3) * 8, (n >> 2) & 1); };
        auto xrel  = [&](int n, uint32_t dep) { if (lane == 0) mbar_arrive(bar_xempty + (n & 3) * 8 + (dep & H.zero)); };
        float* red = reinterpret_cast<float*>(smem + OFF_SS + 8448);
        {
            uint32_t w[4][4][4], xb[4][2];
#pragma unroll
            for (int s = 0; s < 4; s++) {
                const uint32_t* X = reinterpret_cast<const uint32_t*>(smem + OFF_X) + (g & 3) * 256 + 32 * x + 8 * s + t;
                xb[s][0] = X[0]; xb[s][1] = X[4];
            }
            xwait(x >> 1);
            const uint32_t dep = load_wT<4>(w, xr + x * 8192, lane);
            float acc[4][4];
#pragma unroll
            for (int u = 0; u < 4; u++) acc[u][0] = acc[u][1] = acc[u][2] = acc[u][3] = 0.f;
#pragma unroll
            for (int s = 0; s < 4; s++)
#pragma unroll
                for (int mt = 0; mt < 4; mt++) mma(acc[mt], w[s][mt][0], w[s][mt][1], w[s][mt][2], w[s][mt][3], xb[s][0], xb[s][1]);
#pragma unroll
            for (int n = 0; n < 4; n++) xrel(n, dep);
            if (t < 2) {
#pragma unroll
                for (int mt = 0; mt < 4; mt++) {
                    float* r0 = red + (x * 4 + 2 * t) * 64 + 16 * mt + g;
                    r0[0] = acc[mt][0]; r0[8] = acc[mt][2]; r0[64] = acc[mt][1]; r0[72] = acc[mt][3];
                }
            }
            bar_sync(2, 256);
            float s = 0.f;
#pragma unroll
            for (int i = 0; i < 8; i++) s += red[i * 256 + tid];
            st_rlx(qdst, (pack_bf16(0.f, s) & 0xffff0000u) | tag);
        }
        if (tid == 0) TL(6);
        {
            uint32_t w[8][4];
            const int r8 = lane & 7;
            const uint32_t a0 = xr + (16 * x + r8 + 8 * ((lane >> 3) & 1)) * 128 + (((lane >> 4) ^ r8) << 4);
#pragma unroll
            for (int hf = 0; hf < 2; hf++) {
                xwait(4 + hf);
                uint32_t dep = 0;
#pragma unroll
                for (int ks = 0; ks < 4; ks++) { ldsm4(w[4 * hf + ks], (a0 ^ (ks << 5)) + hf * CH_BYTES); dep |= w[4 * hf + ks][0]; }
                xrel(4 + hf, dep);
            }
            if (x < 4) gather128(&H.S->q[1][x][h * 128], tag, smem + OFF_OA + x * 288, lane, QD1);
            bar_sync(2, 256);
            float c[4] = {0.f, 0.f, 0.f, 0.f};
#pragma unroll
            for (int i = 0; i < 8; i++) {
                const uint2 b = *reinterpret_cast<const uint2*>(smem + OFF_OA + (g & 3) * 288 + (16 * i + 4 * t) * 2);
                mma(c, w[i][0], w[i][1], w[i][2], w[i][3], b.x, b.y);
            }
            uint16_t* stg = reinterpret_cast<uint16_t*>(smem + OFF_SS);
            if (t < 2) {
                const int ks = x & 3;
#pragma unroll
                for (int q = 0; q < 4; q++) {
                    const int b = 2 * t + (q & 1), rg = q >> 1;
                    const float vh = bf16_round(c[q]);
                    const int o = b * 256 + (x >> 2) * 128 + (ks >> 1) * 32 + (g >> 1) * 8 + (ks & 1) * 4 + rg * 2 + (g & 1);
                    stg[o]      = (uint16_t)(__float_as_uint(vh) >> 16);
                    stg[o + 64] = (uint16_t)pack_bf16(c[q] - vh, 0.f);
                }
            }
            bar_sync(2, 256);
            if (tid < 128) {
                const uint4 val = reinterpret_cast<const uint4*>(stg)[tid];
                *reinterpret_cast<uint4*>(&H.S->qabs[tid >> 5][2 * j + ((tid >> 4) & 1)][(tid >> 3) & 1][h >> 3][(tid >> 2) & 1][(h & 7) * 4 + (tid & 3)][0]) = val;
            }
            bar_sync(2, 256);
            if (tid == 0) { add_rel(H.S->cntQ); TL(7); }
            if (j == 0 && x == 0) bar_arrive(10, 64);
        }
        if (j == 0) {
            uint32_t qf[2][4][8];
#pragma unroll
            for (int k = 0; k < 4; k++) {
                xwait(6 + k);
                uint32_t dep = 0;
                if (k == (x >> 1)) {
                    const unsigned char* qp = smem + OFF_XR + ((6 + k) & 3) * CH_BYTES + (x & 1) * 8192 + lane * 16;
#pragma unroll
                    for (int i = 0; i < 16; i++) {
                        const uint4 a = *reinterpret_cast<const uint4*>(qp + i * 512);
                        uint32_t* d = &qf[i >> 3][(i >> 1) & 3][4 * (i & 1)];
                        d[0] = a.x; d[1] = a.y; d[2] = a.z; d[3] = a.w;
                        dep |= a.x;
                    }
                }
                xrel(6 + k, dep);
            }
            if (tid == 0) TL(8);
            float acc[4][4][4];
#pragma unroll
            for (int a = 0; a < 4; a++)
#pragma unroll
                for (int b = 0; b < 4; b++) acc[a][b][0] = acc[a][b][1] = acc[a][b][2] = acc[a][b][3] = 0.f;
            float m = -INFINITY, l = 0.f;
            const int r8 = lane & 7;
            const uint32_t koff = x * 2048 + (r8 + 8 * ((lane >> 3) & 1)) * 128 + (((lane >> 4) ^ r8) << 4);
            const uint32_t voff = x * 2048 + (r8 + 8 * (lane >> 4)) * 128 + ((((lane >> 3) & 1) ^ r8) << 4);
            const int sh = tid >> 3, skp = tid & 7;
#define CK0
#define CK1(v)
            for (int n = 10; n < 10 + A_TILES; n++) {
                CK0
                xwait(n);
                CK1(cw)
                const uint32_t base = xr + (n & 3) * CH_BYTES;
                float S[4][4];
#pragma unroll
                for (int nt = 0; nt < 4; nt++) S[nt][0] = S[nt][1] = S[nt][2] = S[nt][3] = 0.f;
#pragma unroll
                for (int ks = 0; ks < 4; ks++) {
                    uint32_t a[4];
                    ldsm4(a, base + (koff ^ (ks << 5)));
#pragma unroll
                    for (int nt = 0; nt < 4; nt++) mma(S[nt], a[0], a[1], a[2], a[3], qf[1][nt][2 * ks], qf[1][nt][2 * ks + 1]);
#pragma unroll
                    for (int nt = 0; nt < 4; nt++) mma(S[nt], a[0], a[1], a[2], a[3], qf[0][nt][2 * ks], qf[0][nt][2 * ks + 1]);
                }
#pragma unroll
                for (int nt = 0; nt < 4; nt++) {
                    unsigned char* sp = smem + OFF_SS + (x * 32 + 8 * nt + 2 * t) * 80 + 8 * g;
                    *reinterpret_cast<float2*>(sp) = make_float2(S[nt][0], S[nt][2]);
                    *reinterpret_cast<float2*>(sp + 80) = make_float2(S[nt][1], S[nt][3]);
                }
                bar_sync(2, 256);
                CK1(c1)
                float s0 = 0.f, s1 = 0.f;
#pragma unroll
                for (int w = 0; w < 8; w++) {
                    const float2 v = *reinterpret_cast<const float2*>(smem + OFF_SS + (w * 32 + sh) * 80 + 8 * skp);
                    s0 += v.x; s1 += v.y;
                }
                s0 = bf16_round(bf16_round(s0) * SCALE);
                s1 = bf16_round(bf16_round(s1) * SCALE);
                float mx = fmaxf(s0, s1);
                mx = fmaxf(mx, __shfl_xor_sync(0xffffffffu, mx, 1));
                mx = fmaxf(mx, __shfl_xor_sync(0xffffffffu, mx, 2));
                mx = fmaxf(mx, __shfl_xor_sync(0xffffffffu, mx, 4));
                mx = fmaxf(mx, m);
                const float al = ex2((m - mx) * LOG2E);
                m = mx;
                const float p0 = ex2((s0 - m) * LOG2E), p1 = ex2((s1 - m) * LOG2E);
                l = l * al + p0 + p1;
                {
                    const uint32_t pp = pack_bf16(p0, p1);
                    uint16_t* dst = reinterpret_cast<uint16_t*>(smem + OFF_SP) + sh * 16 + kperm(skp);
                    dst[0] = (uint16_t)pp; dst[2] = (uint16_t)(pp >> 16);
                }
                if (skp == 0) reinterpret_cast<float*>(smem + OFF_ALPHA)[sh] = al;
                bar_sync(2, 256);
                CK1(c2)
                uint2 pb[4];
#pragma unroll
                for (int nt = 0; nt < 4; nt++) {
                    pb[nt] = *reinterpret_cast<const uint2*>(smem + OFF_SP + (8 * nt + g) * 32 + 8 * t);
                    const float2 a2 = *reinterpret_cast<const float2*>(smem + OFF_ALPHA + (8 * nt + 2 * t) * 4);
#pragma unroll
                    for (int mt = 0; mt < 4; mt++) {
                        acc[mt][nt][0] *= a2.x; acc[mt][nt][1] *= a2.y; acc[mt][nt][2] *= a2.x; acc[mt][nt][3] *= a2.y;
                    }
                }
                uint32_t dep = 0;
#pragma unroll
                for (int mt = 0; mt < 4; mt++) {
                    uint32_t a[4];
                    ldsm4t(a, base + (voff ^ (mt << 5)));
                    dep |= a[0];
#pragma unroll
                    for (int nt = 0; nt < 4; nt++) mma(acc[mt][nt], a[0], a[1], a[2], a[3], pb[nt].x, pb[nt].y);
                }
                xrel(n, dep);
                CK1(c3)
            }
#pragma unroll
            for (int nt = 0; nt < 4; nt++)
#pragma unroll
                for (int e = 0; e < 2; e++) {
                    float* dst = &H.S->pA[8 * nt + 2 * t + e][ab][asplit][64 * x + 4 * g];
                    *reinterpret_cast<float4*>(dst)      = make_float4(acc[0][nt][e], acc[0][nt][2 + e], acc[1][nt][e], acc[1][nt][2 + e]);
                    *reinterpret_cast<float4*>(dst + 32) = make_float4(acc[2][nt][e], acc[2][nt][2 + e], acc[3][nt][e], acc[3][nt][2 + e]);
                }
            l += __shfl_xor_sync(0xffffffffu, l, 1);
            l += __shfl_xor_sync(0xffffffffu, l, 2);
            l += __shfl_xor_sync(0xffffffffu, l, 4);
            if (skp == 0) H.S->mlA[sh][ab][asplit] = make_float2(m, l);
            bar_sync(2, 256);
            if (tid == 0) { add_rel(H.S->cntA); TL(9); }
        } else if (j >= 2) {
            uint32_t wv[4][4][4];
#pragma unroll
            for (int k = 0; k < 4; k++) {
                xwait(6 + k);
                uint32_t dep = 0;
                if (k == (x >> 1)) dep = load_wT<4>(wv, xr + ((6 + k) & 3) * CH_BYTES + (x & 1) * 8192, lane);
                xrel(6 + k, dep);
            }
            {
                const int b = tid >> 6, xx = (tid >> 3) & 7, gg = tid & 7;
                xwait(10 + b);
                if (tid == 0) TL(8);
                const float2* mlp = reinterpret_cast<const float2*>(smem + OFF_MLA) + b * A_SPLITS;
                float mm = -INFINITY, ll = 0.f;
#pragma unroll
                for (int s = 0; s < A_SPLITS; s++) mm = fmaxf(mm, mlp[s].x);
#pragma unroll
                for (int s = 0; s < A_SPLITS; s++) ll += mlp[s].y * ex2((mlp[s].x - mm) * LOG2E);
                const float inv = 1.f / ll;
                float cl[8];
#pragma unroll
                for (int e = 0; e < 8; e++) cl[e] = 0.f;
                const float* src = reinterpret_cast<const float*>(smem + OFF_XR + ((10 + b) & 3) * CH_BYTES) + 64 * xx + 4 * gg;
#pragma unroll
                for (int s = 0; s < A_SPLITS; s++) {
                    const float wt = ex2((mlp[s].x - mm) * LOG2E) * inv;
                    const float4 a = *reinterpret_cast<const float4*>(src + s * 512), c = *reinterpret_cast<const float4*>(src + s * 512 + 32);
                    cl[0] += wt * a.x; cl[1] += wt * a.y; cl[2] += wt * a.z; cl[3] += wt * a.w;
                    cl[4] += wt * c.x; cl[5] += wt * c.y; cl[6] += wt * c.z; cl[7] += wt * c.w;
                }
                uint16_t* hi = reinterpret_cast<uint16_t*>(smem + OFF_SS + b * 1056);
                uint16_t* lo = reinterpret_cast<uint16_t*>(smem + OFF_SS + (b + 4) * 1056);
#pragma unroll
                for (int e = 0; e < 8; e++) {
                    const int c = kperm(64 * xx + 8 * e + gg);
                    const float vh = bf16_round(cl[e]);
                    hi[c] = (uint16_t)(__float_as_uint(vh) >> 16);
                    lo[c] = (uint16_t)pack_bf16(cl[e] - vh, 0.f);
                }
                bar_sync(2, 256);
#pragma unroll
                for (int k = 0; k < 4; k++) xrel(10 + k, __float_as_uint(cl[0]) | __float_as_uint(cl[4]));
            }
            {
                float acc[4][4];
#pragma unroll
                for (int u = 0; u < 4; u++) acc[u][0] = acc[u][1] = acc[u][2] = acc[u][3] = 0.f;
#pragma unroll
                for (int s = 0; s < 4; s++) {
                    const uint2 b = *reinterpret_cast<const uint2*>(smem + OFF_SS + g * 1056 + (64 * x + 16 * s + 4 * t) * 2);
#pragma unroll
                    for (int mt = 0; mt < 4; mt++) mma(acc[mt], wv[s][mt][0], wv[s][mt][1], wv[s][mt][2], wv[s][mt][3], b.x, b.y);
                }
#pragma unroll
                for (int mt = 0; mt < 4; mt++)
#pragma unroll
                    for (int e = 0; e < 4; e++) acc[mt][e] += __shfl_xor_sync(0xffffffffu, acc[mt][e], 2);
                if (t < 2) {
#pragma unroll
                    for (int mt = 0; mt < 4; mt++) {
                        float* r0 = red + (x * 4 + 2 * t) * 64 + 16 * mt + g;
                        r0[0] = acc[mt][0]; r0[8] = acc[mt][2]; r0[64] = acc[mt][1]; r0[72] = acc[mt][3];
                    }
                }
            }
            bar_sync(2, 256);
            {
                float s = 0.f;
#pragma unroll
                for (int i = 0; i < 8; i++) s += red[i * 256 + tid];
                st_rlx(&H.S->vec[0][h][tid >> 6][kperm(64 * (j - 2) + (tid & 63))], (pack_bf16(0.f, s) & 0xffff0000u) | tag);
            }
            if (tid == 0) TL(9);
        }
        {
            __syncwarp();
            if (lane == 0) mbar_arrive(bar_xdone);
#pragma unroll 1
            for (uint32_t pass = H.zero; pass < 2; pass++) {
                if (pass == br) {
                    mbar_wait(br ? bar_cmb + 8 : bar_trig + 16, 0);
#pragma unroll 1
                    for (int u = 2 * x; u < 2 * x + 2; u++)
                        if (u < 15 || hl < HURG) gather128(&H.S->vec[br][hp + 8 * (u >> 2)][u & 3][0], tag, smem + OFF_SS + u * 288, lane, QD1);
                    __syncwarp();
                    if (lane == 0) { mbar_arrive(bar_vec); if (hl < HURG) mbar_arrive(bar_vec + 8); }
                    TL3(13, 0);
                    if (tid == 0) { H.S->epoch[bid] = ep; TL(10); }
                }
                if (pass ? hl >= HURG : (j < 3 || h < HURG)) {
                    const int pr = pass ? 96 + hl : 32 * j + h;
                    const uint32_t* rp = &H.S->pB[64 * pr + 8 * x][lane * 4];
                    const uint32_t* sp = &H.S->mlB[64 * pr + 8 * x + (lane & 7)][0];
                    uint4 v[8], sv;
                    mbar_wait(bar_cmb + pass * 16, 0);
                    TL3(5, 0);
                    if (lane == 0) {
                        mbar_expect_tx(bar_gat + x * 8, 4096 + 256);
                        bulk_load_nh(xr + x * 4096, rp, 4096, bar_gat + x * 8);
                        bulk_load_nh(sb + OFF_ST + x * 256, sp, 256, bar_gat + x * 8);
                    }
                    __syncwarp();
                    mbar_wait(bar_gat + x * 8, pass);
                    TL3(15, 0);
                    sv = lds128(sb + OFF_ST + x * 256 + (lane & 7) * 32);
#pragma unroll
                    for (int i = 0; i < 8; i++) v[i] = lds128(xr + x * 4096 + i * 512 + lane * 16);
                    float mx, ll, wt[8];
#pragma unroll 1
                    for (uint32_t it = 0;; it++) {
                        uint32_t bad[9];
#pragma unroll
                        for (int i = 0; i < 8; i++) bad[i] = untagged(v[i], par);
                        bad[8] = untagged(sv, par);
                        const uint32_t anyb = or3(or3(bad[0], bad[1], bad[2]), or3(bad[3], bad[4], bad[5]), or3(bad[6], bad[7], bad[8]));
                        const float m0 = __uint_as_float(sv.y);
                        mx = warp_max(m0);
                        const float w0 = ex2((m0 - mx) * LOG2E);
                        ll = w0 * __uint_as_float(sv.x);
                        const float l4 = __shfl_xor_sync(0xffffffffu, ll, 4);
#pragma unroll
                        for (int i = 0; i < 8; i++) wt[i] = __shfl_sync(0xffffffffu, w0, i);
                        ll += l4;
                        ll += __shfl_xor_sync(0xffffffffu, ll, 2);
                        if (!__any_sync(0xffffffffu, anyb & 1) || it >= SPIN_LIMIT) break;
                        uint32_t mask = 0;
#pragma unroll
                        for (int i = 0; i < 9; i++) mask |= (bad[i] & 1) << i;
                        const uint32_t pend = __reduce_or_sync(0xffffffffu, mask);
                        ld_rlx2x64_if(sv, sp, pend & 256);
#pragma unroll
                        for (int i = 0; i < 8; i++) ld_rlx2x64_if(v[i], rp + i * 128, pend & (1 << i));
                    }
                    ll += __shfl_xor_sync(0xffffffffu, ll, 1);
                    float4 acc = make_float4(0.f, 0.f, 0.f, 0.f), acd = acc;
#pragma unroll
                    for (int i = 0; i < 8; i += 2) {
                        acc.x += wt[i] * __uint_as_float(v[i].x); acc.y += wt[i] * __uint_as_float(v[i].y);
                        acc.z += wt[i] * __uint_as_float(v[i].z); acc.w += wt[i] * __uint_as_float(v[i].w);
                        acd.x += wt[i + 1] * __uint_as_float(v[i + 1].x); acd.y += wt[i + 1] * __uint_as_float(v[i + 1].y);
                        acd.z += wt[i + 1] * __uint_as_float(v[i + 1].z); acd.w += wt[i + 1] * __uint_as_float(v[i + 1].w);
                    }
                    acc.x += acd.x; acc.y += acd.y; acc.z += acd.z; acc.w += acd.w;
                    TL3(6, 0);
                    if (lane == 0) reinterpret_cast<float2*>(red + 1024)[x] = make_float2(mx, ll);
                    reinterpret_cast<float4*>(red)[tid] = acc;
                    const int d = kperm(16 * ((tid >> 2) & 3) + 8 * (tid & 1) + 64 * ((tid >> 1) & 1) + ((tid >> 4) & 7));
                    uint32_t od = sb + OFF_SS + 15 * 288 + 2 * d, ra = sb + OFF_SS + 8448;
                    asm volatile("" : "+r"(od), "+r"(ra));
                    bar_sync(2, 256);
                    if (x < 4) {
                        uint4 st[4];
                        float r[8];
#pragma unroll
                        for (int i = 0; i < 4; i++) st[i] = lds128(ra + 4096 + 16 * i);
#pragma unroll
                        for (int i = 0; i < 8; i++) r[i] = lds32(ra + 512 * i + 4 * tid);
                        float m2[4];
#pragma unroll
                        for (int i = 0; i < 4; i++) m2[i] = fmaxf(__uint_as_float(st[i].x), __uint_as_float(st[i].z));
                        const float mm = fmaxf(fmaxf(m2[0], m2[1]), fmaxf(m2[2], m2[3]));
                        float s0 = 0.f, s1 = 0.f, l0 = 0.f, l1 = 0.f;
#pragma unroll
                        for (int i = 0; i < 4; i++) {
                            const float f0 = ex2((__uint_as_float(st[i].x) - mm) * LOG2E), f1 = ex2((__uint_as_float(st[i].z) - mm) * LOG2E);
                            s0 += f0 * r[2 * i]; s1 += f1 * r[2 * i + 1];
                            l0 += f0 * __uint_as_float(st[i].y); l1 += f1 * __uint_as_float(st[i].w);
                        }
                        float inv;
                        asm("rcp.approx.ftz.f32 %0, %1;" : "=f"(inv) : "f"(l0 + l1));
                        const uint32_t ob = pack_bf16((s0 + s1) * inv, 0.f);
                        if (pass) asm volatile("st.shared.u16 [%0], %1;" :: "r"(od), "h"((uint16_t)ob) : "memory");
                        else st_rlx(&H.S->vec[1][h][j][d], (ob << 16) | tag);
                    }
                    __syncwarp();
                    if (pass && lane == 0) mbar_arrive(bar_vec + 8);
                    TL3(7, 0);
                    if (!pass) bar_sync(2, 256);
                }
            }
        }
    }
}

typedef CUresult (*EncodeFn)(CUtensorMap*, CUtensorMapDataType, cuuint32_t, void*, const cuuint64_t*, const cuuint64_t*,
                             const cuuint32_t*, const cuuint32_t*, CUtensorMapInterleave, CUtensorMapSwizzle,
                             CUtensorMapL2promotion, CUtensorMapFloatOOBfill);

void encode2d(EncodeFn fn, CUtensorMap* tm, void* ptr, uint64_t cols, uint64_t rows, uint32_t box_rows) {
    const cuuint64_t dims[2] = {cols, rows};
    const cuuint64_t strides[1] = {cols * 2};
    const cuuint32_t box[2] = {64, box_rows};
    const cuuint32_t es[2] = {1, 1};
    fn(tm, CU_TENSOR_MAP_DATA_TYPE_BFLOAT16, 2, ptr, dims, strides, box, es, CU_TENSOR_MAP_INTERLEAVE_NONE,
       CU_TENSOR_MAP_SWIZZLE_128B, CU_TENSOR_MAP_L2_PROMOTION_NONE, CU_TENSOR_MAP_FLOAT_OOB_FILL_NONE);
}

}

extern "C" void kernel_launch(void* const* d_in, const int* in_sizes, int n_in, void* d_out, int out_size) {
    (void)in_sizes; (void)n_in; (void)out_size;
    static EncodeFn encode = nullptr;
    static Scratch* scratch = nullptr;
    if (!encode) {
        cudaFuncSetAttribute(fused_decode_kernel, cudaFuncAttributeMaxDynamicSharedMemorySize, SMEM_BYTES + SMEM_EXTRA);
        void* fn = nullptr;
        cudaDriverEntryPointQueryResult qr;
        cudaGetDriverEntryPoint("cuTensorMapEncodeTiled", &fn, cudaEnableDefault, &qr);
        encode = (EncodeFn)fn;
        void* sp = nullptr;
        cudaGetSymbolAddress(&sp, g_scratch);
        scratch = (Scratch*)sp;
    }
    Params p;
    encode2d(encode, &p.tm_wq[0], d_in[9], 4096, 512, 128);
    encode2d(encode, &p.tm_wq[1], d_in[2], 4096, 512, 128);
    encode2d(encode, &p.tm_wuk,   d_in[3], 4096, 512, 128);
    encode2d(encode, &p.tm_wuv,   d_in[4], 4096, 512, 128);
    encode2d(encode, &p.tm_wo[1], d_in[10], 512, 4096, 128);
    encode2d(encode, &p.tm_wo[0], d_in[5], 512, 4096, 128);
    {
        const cuuint64_t dims[3] = {64, 16384, 8};
        const cuuint64_t strides[2] = {1024, 128};
        const cuuint32_t box[3] = {64, 16, 8};
        const cuuint32_t es[3] = {1, 1, 1};
        encode(&p.tm_ckv, CU_TENSOR_MAP_DATA_TYPE_BFLOAT16, 3, d_in[1], dims, strides, box, es, CU_TENSOR_MAP_INTERLEAVE_NONE,
               CU_TENSOR_MAP_SWIZZLE_128B, CU_TENSOR_MAP_L2_PROMOTION_NONE, CU_TENSOR_MAP_FLOAT_OOB_FILL_NONE);
    }
    p.wo[0] = (const __nv_bfloat16*)d_in[5];
    p.wo[1] = (const __nv_bfloat16*)d_in[10];
    p.out = (__nv_bfloat16*)d_out;
    Hot hp;
    hp.kp = (const char*)d_in[7];
    hp.vp = (const char*)d_in[8];
    hp.S = scratch;
    hp.x[0] = (const __nv_bfloat16*)d_in[6];
    hp.x[1] = (const __nv_bfloat16*)d_in[0];
    hp.zero = 0;
    hp.never = 0;
    cudaLaunchConfig_t cfg = {};
    cfg.gridDim = dim3(NCTA);
    cfg.blockDim = dim3(NTHREADS);
    cfg.dynamicSmemBytes = SMEM_BYTES + SMEM_EXTRA;
    cfg.stream = cudaStreamPerThread;
    cudaLaunchAttribute at[1];
    at[0].id = cudaLaunchAttributeCooperative;
    at[0].val.cooperative = 1;
    cfg.attrs = at;
    cfg.numAttrs = 1;
    cudaLaunchKernelEx(&cfg, fused_decode_kernel, hp, p);
}
```
